```python
import torch

def _softmax(x, axis=-1):
    return torch.softmax(x, dim=axis)
def _gelu(x):
    return torch.nn.functional.gelu(x, approximate="tanh")
def _silu(x):
    return torch.nn.functional.silu(x)
def _sigmoid(x):
    return torch.sigmoid(x)
def _layernorm(x, axis=-1, eps=1e-5):
    m = x.mean(dim=axis, keepdim=True)
    v = x.var(dim=axis, keepdim=True, unbiased=False)
    return (x - m) / torch.sqrt(v + eps)
def _scatter_add(tgt, idx, src, axis=0):
    return tgt.clone().index_add_(axis, idx, src)
def _segment_sum(src, seg, n):
    out = torch.zeros((n,) + src.shape[1:], dtype=src.dtype)
    return out.index_add_(0, seg, src)
def _pad(x, pw):
    flat = tuple(v for pair in reversed(pw) for v in pair)
    return torch.nn.functional.pad(x, flat)

kernel_name = 'standalone__geglu_ffn__prompt'

def setup_inputs():

    _w = (lambda a: (lambda t: t.to(torch.bfloat16) if t.is_floating_point() else t)(torch.as_tensor(a)))
    B, S, D, F = 1, 2048, 1024, 3584
    return {
        "x": _w((lambda *s: torch.randn(*s, dtype=torch.bfloat16) * 0.05)(B, S, D)),
        "w_gate": _w((lambda *s: torch.randn(*s, dtype=torch.bfloat16) * 0.05)(D, F)),
        "w_up": _w((lambda *s: torch.randn(*s, dtype=torch.bfloat16) * 0.05)(D, F)),
        "w_down": _w((lambda *s: torch.randn(*s, dtype=torch.bfloat16) * 0.05)(F, D)),
    }

def reference(x, w_gate, w_up, w_down):
    return (_gelu(x @ w_gate) * (x @ w_up)) @ w_down
```

```cpp
#include <cuda_runtime.h>
#include <cuda_bf16.h>
#include <cuda.h>
#include <stdint.h>

namespace {

constexpr int M_TOK = 2048, D_MODEL = 1024, D_FF = 3584;
constexpr int KB_FF = D_FF / 64;
constexpr int NUM_CTAS = 128;
constexpr int NUM_THREADS = 384;

constexpr int STA = 4, STA_BYTES = 49152;
constexpr int STB = 6, STB_BYTES = 32768;
constexpr int RING_BYTES = STA * STA_BYTES;
constexpr int STAGING_OFF = RING_BYTES;
constexpr int BAR_OFF = STAGING_OFF + 32768;
constexpr int SMEM_BYTES = BAR_OFF + 256 + 1024;

constexpr int BAR_FULL_A = 0, BAR_EMPTY_A = 4, BAR_FULL_B = 8, BAR_EMPTY_B = 14, BAR_SFULL = 20, BAR_SEMPTY = 22;

__device__ __align__(1024) uint8_t g_h[(size_t)M_TOK * D_FF * 2];
__device__ unsigned int g_ready[32 * 4];
__device__ unsigned int g_done;

#define TS(slot, cond)

__device__ __forceinline__ uint32_t smem_u32(const void* p) { return (uint32_t)__cvta_generic_to_shared(p); }
__device__ __forceinline__ void mbar_init(uint32_t bar, uint32_t cnt) {
    asm volatile("mbarrier.init.shared::cta.b64 [%0], %1;" :: "r"(bar), "r"(cnt) : "memory");
}
__device__ __forceinline__ void mbar_expect_tx(uint32_t bar, uint32_t bytes) {
    asm volatile("mbarrier.arrive.expect_tx.shared::cta.b64 _, [%0], %1;" :: "r"(bar), "r"(bytes) : "memory");
}
__device__ __forceinline__ void mbar_arrive(uint32_t bar) {
    asm volatile("mbarrier.arrive.shared::cta.b64 _, [%0];" :: "r"(bar) : "memory");
}
__device__ __forceinline__ void mbar_arrive_remote(uint32_t cluster_addr) {
    asm volatile("mbarrier.arrive.shared::cluster.b64 _, [%0];" :: "r"(cluster_addr) : "memory");
}
__device__ __forceinline__ uint32_t mapa(uint32_t addr, uint32_t cta) {
    uint32_t r;
    asm("mapa.shared::cluster.u32 %0, %1, %2;" : "=r"(r) : "r"(addr), "r"(cta));
    return r;
}
__device__ __forceinline__ bool mbar_try(uint32_t bar, uint32_t parity) {
    uint32_t done;
    asm volatile("{\n.reg .pred p;\nmbarrier.try_wait.parity.shared::cta.b64 p, [%1], %2;\nselp.u32 %0, 1, 0, p;\n}"
                 : "=r"(done) : "r"(bar), "r"(parity) : "memory");
    return done != 0;
}
__device__ __forceinline__ void mbar_wait_p(uint32_t bar, uint32_t parity) {
    uint32_t it = 0;
    while (!mbar_try(bar, parity)) {
        if (++it > (1u << 20)) __trap();
    }
}
__device__ __forceinline__ void mbar_wait(uint32_t bar, uint32_t parity) {
    if (mbar_try(bar, parity)) return;
    uint32_t it = 0;
    while (!mbar_try(bar, parity)) {
        if (++it > (1u << 21)) break;
    }
}
__device__ __forceinline__ void tma_2d(uint32_t dst, const CUtensorMap* m, uint32_t bar, int c0, int c1) {
    asm volatile("cp.async.bulk.tensor.2d.shared::cluster.global.mbarrier::complete_tx::bytes [%0], [%1, {%3, %4}], [%2];"
                 :: "r"(dst), "l"((uint64_t)m), "r"(bar), "r"(c0), "r"(c1) : "memory");
}
__device__ __forceinline__ void tma_2d_mc(uint32_t dst, const CUtensorMap* m, uint32_t bar, int c0, int c1) {
    asm volatile("cp.async.bulk.tensor.2d.shared::cluster.global.mbarrier::complete_tx::bytes.multicast::cluster [%0], [%1, {%3, %4}], [%2], %5;"
                 :: "r"(dst), "l"((uint64_t)m), "r"(bar), "r"(c0), "r"(c1), "h"((uint16_t)3) : "memory");
}
__device__ __forceinline__ void tma_3d(uint32_t dst, const CUtensorMap* m, uint32_t bar, int c0, int c1, int c2) {
    asm volatile("cp.async.bulk.tensor.3d.shared::cluster.global.mbarrier::complete_tx::bytes [%0], [%1, {%3, %4, %5}], [%2];"
                 :: "r"(dst), "l"((uint64_t)m), "r"(bar), "r"(c0), "r"(c1), "r"(c2) : "memory");
}
__device__ __forceinline__ void tma_3d_mc(uint32_t dst, const CUtensorMap* m, uint32_t bar, int c0, int c1, int c2) {
    asm volatile("cp.async.bulk.tensor.3d.shared::cluster.global.mbarrier::complete_tx::bytes.multicast::cluster [%0], [%1, {%3, %4, %5}], [%2], %6;"
                 :: "r"(dst), "l"((uint64_t)m), "r"(bar), "r"(c0), "r"(c1), "r"(c2), "h"((uint16_t)3) : "memory");
}
__device__ __forceinline__ void bulk_load_mc(uint32_t dst, const void* src, uint32_t bytes, uint32_t bar) {
    asm volatile("cp.async.bulk.shared::cluster.global.mbarrier::complete_tx::bytes.multicast::cluster [%0], [%1], %2, [%3], %4;"
                 :: "r"(dst), "l"(src), "r"(bytes), "r"(bar), "h"((uint16_t)3) : "memory");
}
__device__ __forceinline__ void bulk_store(void* dst, uint32_t src, uint32_t bytes) {
    asm volatile("cp.async.bulk.global.shared::cta.bulk_group [%0], [%1], %2;" :: "l"(dst), "r"(src), "r"(bytes) : "memory");
}
__device__ __forceinline__ void tma_store_2d(const CUtensorMap* m, uint32_t src, int c0, int c1) {
    asm volatile("cp.async.bulk.tensor.2d.global.shared::cta.bulk_group [%0, {%2, %3}], [%1];"
                 :: "l"((uint64_t)m), "r"(src), "r"(c0), "r"(c1) : "memory");
}
__device__ __forceinline__ void prefetch_map(const CUtensorMap* m) {
    asm volatile("prefetch.tensormap [%0];" :: "l"((uint64_t)m) : "memory");
}
__device__ __forceinline__ void bulk_commit() { asm volatile("cp.async.bulk.commit_group;" ::: "memory"); }
__device__ __forceinline__ void fence_async_smem() { asm volatile("fence.proxy.async.shared::cta;" ::: "memory"); }
__device__ __forceinline__ void cluster_arrive() { asm volatile("barrier.cluster.arrive.release.aligned;" ::: "memory"); }
__device__ __forceinline__ void cluster_wait() { asm volatile("barrier.cluster.wait.acquire.aligned;" ::: "memory"); }
__device__ __forceinline__ void wg_fence() { asm volatile("wgmma.fence.sync.aligned;" ::: "memory"); }
__device__ __forceinline__ void wg_commit() { asm volatile("wgmma.commit_group.sync.aligned;" ::: "memory"); }
template <int N> __device__ __forceinline__ void wg_wait() { asm volatile("wgmma.wait_group.sync.aligned %0;" :: "n"(N) : "memory"); }

constexpr uint64_t DESC_A_HI = (1ull << 62) | (64ull << 32) | (1ull << 16);
constexpr uint64_t DESC_B_HI = (1ull << 62) | (64ull << 32) | (512ull << 16);
__device__ __forceinline__ uint64_t desc_a(uint32_t addr) { return DESC_A_HI | (uint64_t)((addr & 0x3FFFF) >> 4); }
__device__ __forceinline__ uint64_t desc_b(uint32_t addr) { return DESC_B_HI | (uint64_t)((addr & 0x3FFFF) >> 4); }

#define R8(a, o) "+f"(a[o + 0]), "+f"(a[o + 1]), "+f"(a[o + 2]), "+f"(a[o + 3]), "+f"(a[o + 4]), "+f"(a[o + 5]), "+f"(a[o + 6]), "+f"(a[o + 7])
#define R32(a, o) R8(a, o), R8(a, o + 8), R8(a, o + 16), R8(a, o + 24)

__device__ __forceinline__ void wgmma_n256(float (&d)[128], uint64_t da, uint64_t db, int scale_d) {
    asm volatile("{\n.reg .pred p;\nsetp.ne.b32 p, %130, 0;\n"
        "wgmma.mma_async.sync.aligned.m64n256k16.f32.bf16.bf16 "
        "{%0,%1,%2,%3,%4,%5,%6,%7,%8,%9,%10,%11,%12,%13,%14,%15,%16,%17,%18,%19,%20,%21,%22,%23,%24,%25,%26,%27,%28,%29,%30,%31,"
        "%32,%33,%34,%35,%36,%37,%38,%39,%40,%41,%42,%43,%44,%45,%46,%47,%48,%49,%50,%51,%52,%53,%54,%55,%56,%57,%58,%59,%60,%61,%62,%63,"
        "%64,%65,%66,%67,%68,%69,%70,%71,%72,%73,%74,%75,%76,%77,%78,%79,%80,%81,%82,%83,%84,%85,%86,%87,%88,%89,%90,%91,%92,%93,%94,%95,"
        "%96,%97,%98,%99,%100,%101,%102,%103,%104,%105,%106,%107,%108,%109,%110,%111,%112,%113,%114,%115,%116,%117,%118,%119,%120,%121,%122,%123,%124,%125,%126,%127},"
        " %128, %129, p, 1, 1, 0, 1;\n}\n"
        : R32(d, 0), R32(d, 32), R32(d, 64), R32(d, 96)
        : "l"(da), "l"(db), "r"(scale_d));
}
__device__ __forceinline__ void wgmma_n128(float (&d)[64], uint64_t da, uint64_t db, int scale_d) {
    asm volatile("{\n.reg .pred p;\nsetp.ne.b32 p, %66, 0;\n"
        "wgmma.mma_async.sync.aligned.m64n128k16.f32.bf16.bf16 "
        "{%0,%1,%2,%3,%4,%5,%6,%7,%8,%9,%10,%11,%12,%13,%14,%15,%16,%17,%18,%19,%20,%21,%22,%23,%24,%25,%26,%27,%28,%29,%30,%31,"
        "%32,%33,%34,%35,%36,%37,%38,%39,%40,%41,%42,%43,%44,%45,%46,%47,%48,%49,%50,%51,%52,%53,%54,%55,%56,%57,%58,%59,%60,%61,%62,%63},"
        " %64, %65, p, 1, 1, 0, 1;\n}\n"
        : R32(d, 0), R32(d, 32)
        : "l"(da), "l"(db), "r"(scale_d));
}
template <int N> __device__ __forceinline__ void fence_regs(float (&d)[N]) {
#pragma unroll
    for (int i = 0; i < N; i++) asm volatile("" : "+f"(d[i]) :: "memory");
}

__device__ __forceinline__ uint32_t pack_bf16(float lo, float hi) {
    uint32_t r;
    asm("cvt.rn.bf16x2.f32 %0, %1, %2;" : "=r"(r) : "f"(hi), "f"(lo));
    return r;
}
__device__ __forceinline__ float geglu(float g, float u) {
    const float K0 = -2.3022081986f;
    const float K1 = -0.1029432397f;
    float t = g * fmaf(g * g, K1, K0);
    float e, r;
    asm("ex2.approx.ftz.f32 %0, %1;" : "=f"(e) : "f"(t));
    asm("rcp.approx.ftz.f32 %0, %1;" : "=f"(r) : "f"(1.0f + e));
    return (g * u) * r;
}
__device__ __forceinline__ uint32_t geglu2(uint32_t g, uint32_t u) {
    float lo = geglu(__uint_as_float(g << 16), __uint_as_float(u << 16));
    float hi = geglu(__uint_as_float(g & 0xffff0000u), __uint_as_float(u & 0xffff0000u));
    return pack_bf16(lo, hi);
}
__device__ __forceinline__ void stsm_x4(uint32_t addr, uint32_t r0, uint32_t r1, uint32_t r2, uint32_t r3) {
    asm volatile("stmatrix.sync.aligned.m8n8.x4.shared.b16 [%0], {%1, %2, %3, %4};"
                 :: "r"(addr), "r"(r0), "r"(r1), "r"(r2), "r"(r3) : "memory");
}

struct Consumer {
    uint32_t base;
    uint32_t bars;
    uint32_t rel;
    uint32_t st_row;
    uint32_t st_sw;
    uint32_t a_off;
    int lane, wg;

    __device__ __forceinline__ void release(int bar_idx) const {
        if (lane < 2) mbar_arrive_remote(rel + 8 * bar_idx);
    }
    __device__ __forceinline__ void stage(int c, uint32_t r0, uint32_t r1, uint32_t r2, uint32_t r3) const {
        stsm_x4(st_row + (c >> 2) * 8192 + (st_sw ^ ((c & 3) << 5)), r0, r1, r2, r3);
    }
    __device__ __forceinline__ void stage_done() const {
        fence_async_smem();
        __syncwarp();
        if (lane == 0) mbar_arrive(bars + 8 * (BAR_SFULL + wg));
    }
    __device__ __forceinline__ void issue_a(float (&acc)[128], int s, uint32_t parity, bool first) const {
        mbar_wait(bars + 8 * (BAR_FULL_A + s), parity);
        uint32_t a = base + s * STA_BYTES;
        uint64_t da = desc_a(a + a_off), db = desc_b(a + 16384);
        wg_fence();
        wgmma_n256(acc, da, db, first ? 0 : 1);
        wgmma_n256(acc, da + 2, db + 128, 1);
        wgmma_n256(acc, da + 4, db + 256, 1);
        wgmma_n256(acc, da + 6, db + 384, 1);
        wg_commit();
    }
    __device__ __forceinline__ void issue_b(float (&acc)[64], int s, uint32_t parity, bool first) const {
        mbar_wait(bars + 8 * (BAR_FULL_B + s), parity);
        uint32_t a = base + s * STB_BYTES;
        uint64_t da = desc_a(a + a_off), db = desc_b(a + 16384);
        wg_fence();
        wgmma_n128(acc, da, db, first ? 0 : 1);
        wgmma_n128(acc, da + 2, db + 128, 1);
        wgmma_n128(acc, da + 4, db + 256, 1);
        wgmma_n128(acc, da + 6, db + 384, 1);
        wg_commit();
    }
};

__global__ void __cluster_dims__(2, 1, 1) __launch_bounds__(NUM_THREADS, 1)
geglu_ffn_kernel(const __grid_constant__ CUtensorMap tm_x128, const __grid_constant__ CUtensorMap tm_x64,
                 const __grid_constant__ CUtensorMap tm_g2, const __grid_constant__ CUtensorMap tm_u2,
                 const __grid_constant__ CUtensorMap tm_g1, const __grid_constant__ CUtensorMap tm_u1,
                 const __grid_constant__ CUtensorMap tm_d, const __grid_constant__ CUtensorMap tm_out) {
    extern __shared__ uint8_t smem_raw[];
    const uint32_t base = (smem_u32(smem_raw) + 1023) & ~1023u;
    const uint32_t bars = base + BAR_OFF;
    const int warp = __shfl_sync(0xffffffffu, threadIdx.x >> 5, 0);
    const int lane = threadIdx.x & 31;
    const int rank = blockIdx.x & 1;
    const int cid = blockIdx.x >> 1;
    const int m_a = (cid & 7) * 2 + rank;
    const int j_a = cid >> 3;
    const int m_b = cid >> 2;
    const int n_b = (cid & 3) * 2 + rank;

    TS(0, threadIdx.x == 0);
    if (threadIdx.x == 256) {
        for (int s = 0; s < STA; s++) { mbar_init(bars + 8 * (BAR_FULL_A + s), 1); mbar_init(bars + 8 * (BAR_EMPTY_A + s), 16); }
        for (int s = 0; s < STB; s++) { mbar_init(bars + 8 * (BAR_FULL_B + s), 1); mbar_init(bars + 8 * (BAR_EMPTY_B + s), 16); }
        for (int w = 0; w < 2; w++) { mbar_init(bars + 8 * (BAR_SFULL + w), 4); mbar_init(bars + 8 * (BAR_SEMPTY + w), 1); }
        asm volatile("fence.mbarrier_init.release.cluster;" ::: "memory");
        prefetch_map(&tm_x128);
        prefetch_map(rank ? &tm_u2 : &tm_g2);
    }
    __syncwarp();
    cluster_arrive();
    cluster_wait();

    if (warp >= 8) {
        asm volatile("setmaxnreg.dec.sync.aligned.u32 24;");
        if (warp == 8) {
            if (lane == 0) {
                const CUtensorMap* tm_w = rank ? &tm_u2 : &tm_g2;
                for (int i = 0; i < 48; i++) {
                    const int s = i & 3, kb = i & 15, t = i >> 4;
                    const uint32_t full = bars + 8 * (BAR_FULL_A + s), a = base + s * STA_BYTES;
                    mbar_wait_p(bars + 8 * (BAR_EMPTY_A + s), ((i >> 2) & 1) ^ 1);
                    mbar_expect_tx(full, STA_BYTES);
                    tma_2d(a, &tm_x128, full, kb * 64, m_a * 128);
                    tma_3d_mc(a + 16384 + rank * 16384, tm_w, full, 0, kb * 64, t * 16 + j_a * 2);
                }
                const uint8_t* h_src = g_h + (size_t)(m_b * 2 + rank) * KB_FF * 8192;
                const unsigned int* ready = g_ready + (m_b * 2 + rank) * 4;
                int s = 0;
                uint32_t ph = 1;
                for (int i = 0; i < 72; i++) {
                    const uint32_t full = bars + 8 * (BAR_FULL_B + s), a = base + s * STB_BYTES;
                    if (i < STB) mbar_wait_p(bars + 8 * (BAR_EMPTY_A + ((2 * i + 1) / 3)), 1);
                    else mbar_wait_p(bars + 8 * (BAR_EMPTY_B + s), ph);
                    mbar_expect_tx(full, STB_BYTES);
                    if (i < 16) {
                        tma_2d_mc(a + rank * 8192, &tm_x64, full, i * 64, m_b * 128 + rank * 64);
                        tma_3d(a + 16384, &tm_g1, full, 0, i * 64, 48 + n_b);
                        tma_3d(a + 24576, &tm_u1, full, 0, i * 64, 48 + n_b);
                    } else {
                        const int kk = i - 16;
                        tma_3d(a + 16384, &tm_d, full, 0, kk * 64, n_b * 2);
                        if ((kk & 15) == 0) {
                            uint32_t v, it = 0;
                            while (true) {
                                asm volatile("ld.acquire.gpu.global.u32 %0, [%1];" : "=r"(v) : "l"(ready + (kk >> 4)) : "memory");
                                if (v >= 8) break;
                                if (++it > (1u << 22)) __trap();
                            }
                            asm volatile("fence.proxy.async.global;" ::: "memory");
                        }
                        bulk_load_mc(a + rank * 8192, h_src + (size_t)kk * 8192, 8192, full);
                    }
                    if (++s == STB) { s = 0; ph ^= 1; }
                }
                __threadfence();
                if (atomicAdd(&g_done, 1) == NUM_CTAS - 1) {
                    __threadfence();
                    for (int i = 0; i < 32 * 4; i++) g_ready[i] = 0;
                    g_done = 0;
                }
            }
        } else if (warp <= 10) {
            if (lane == 0) {
                const int w = warp - 9;
                const uint32_t src = base + STAGING_OFF + w * 16384;
                for (int t = 0; t < 4; t++) {
                    const int m64 = (t < 3 ? m_a : m_b) * 2 + w;
                    const int kb0 = t < 3 ? t * 16 + j_a * 2 : 48 + n_b;
                    mbar_wait_p(bars + 8 * (BAR_SFULL + w), t & 1);
                    bulk_store(g_h + ((size_t)m64 * KB_FF + kb0) * 8192, src, t < 3 ? 16384 : 8192);
                    bulk_commit();
                    asm volatile("cp.async.bulk.wait_group 0;" ::: "memory");
                    mbar_arrive(bars + 8 * (BAR_SEMPTY + w));
                    asm volatile("fence.proxy.async.global;" ::: "memory");
                    asm volatile("red.release.gpu.global.add.u32 [%0], 1;" :: "l"(g_ready + m64 * 4 + t) : "memory");
                }
            }
        }
        __syncwarp();
        cluster_arrive();
        cluster_wait();
    } else {
        asm volatile("setmaxnreg.inc.sync.aligned.u32 240;");
        Consumer c;
        c.base = base;
        c.bars = bars;
        c.lane = lane;
        c.wg = warp >> 2;
        c.rel = mapa(bars, lane & 1);
        c.a_off = c.wg * 8192;
        c.st_row = base + STAGING_OFF + c.wg * 16384 + ((warp & 3) * 16 + (lane & 15)) * 128;
        c.st_sw = ((lane >> 4) ^ (lane & 7)) << 4;
        const uint32_t sempty = bars + 8 * (BAR_SEMPTY + c.wg);

        float acc[128];
        uint32_t pk[64];
#pragma unroll
        for (int i = 0; i < 64; i++) pk[i] = 0;

#pragma unroll 1
        for (int t = 0; t < 3; t++) {
#pragma unroll
            for (int kb = 0; kb < 8; kb++) {
                c.issue_a(acc, kb & 3, (kb >> 2) & 1, kb == 0);
                TS(1, kb == 0 && t == 0 && threadIdx.x == 0);
                if (kb > 0) { wg_wait<1>(); c.release(BAR_EMPTY_A + ((kb - 1) & 3)); }
                if (t > 0) {
                    if (kb == 0) mbar_wait(sempty, (t & 1));
                    c.stage(kb, geglu2(pk[4 * kb], pk[32 + 4 * kb]), geglu2(pk[4 * kb + 1], pk[33 + 4 * kb]),
                            geglu2(pk[4 * kb + 2], pk[34 + 4 * kb]), geglu2(pk[4 * kb + 3], pk[35 + 4 * kb]));
                    if (kb == 7) c.stage_done();
                }
            }
#pragma unroll 1
            for (int kb = 8; kb < 16; kb++) {
                c.issue_a(acc, kb & 3, (kb >> 2) & 1, false);
                wg_wait<1>();
                c.release(BAR_EMPTY_A + ((kb - 1) & 3));
            }
            wg_wait<0>();
            fence_regs(acc);
            c.release(BAR_EMPTY_A + 3);
#pragma unroll
            for (int i = 0; i < 64; i++) pk[i] = pack_bf16(acc[2 * i], acc[2 * i + 1]);
            TS(2 + t, threadIdx.x == 0);
        }

        float acc3[64];
#pragma unroll
        for (int kb = 0; kb < 8; kb++) {
            c.issue_b(acc3, kb % STB, (kb / STB) & 1, kb == 0);
            if (kb > 0) { wg_wait<1>(); c.release(BAR_EMPTY_B + (kb - 1) % STB); }
            if (kb == 0) mbar_wait(sempty, 1);
            c.stage(kb, geglu2(pk[4 * kb], pk[32 + 4 * kb]), geglu2(pk[4 * kb + 1], pk[33 + 4 * kb]),
                    geglu2(pk[4 * kb + 2], pk[34 + 4 * kb]), geglu2(pk[4 * kb + 3], pk[35 + 4 * kb]));
            if (kb == 7) c.stage_done();
        }
        int s = 8 % STB, ps = 7 % STB;
        uint32_t ph = (8 / STB) & 1;
#pragma unroll 1
        for (int kb = 8; kb < 16; kb++) {
            c.issue_b(acc3, s, ph, false);
            wg_wait<1>();
            c.release(BAR_EMPTY_B + ps);
            ps = s;
            if (++s == STB) { s = 0; ph ^= 1; }
        }
        TS(5, threadIdx.x == 0);

        float acc4[64];
#pragma unroll
        for (int kb = 0; kb < 4; kb++) {
            c.issue_b(acc4, (16 + kb) % STB, ((16 + kb) / STB) & 1, kb == 0);
            wg_wait<1>();
            c.release(BAR_EMPTY_B + (15 + kb) % STB);
            if (kb == 0) { fence_regs(acc3); mbar_wait(sempty, 0); }
            uint32_t r[4];
#pragma unroll
            for (int q = 0; q < 4; q++) {
                const int i = 8 * kb + 2 * q;
                r[q] = geglu2(pack_bf16(acc3[i], acc3[i + 1]), pack_bf16(acc3[32 + i], acc3[33 + i]));
            }
            c.stage(kb, r[0], r[1], r[2], r[3]);
            if (kb == 3) c.stage_done();
        }
        s = 20 % STB; ps = 19 % STB; ph = (20 / STB) & 1;
#pragma unroll 1
        for (int kb = 4; kb < KB_FF; kb++) {
            c.issue_b(acc4, s, ph, false);
            wg_wait<1>();
            c.release(BAR_EMPTY_B + ps);
            ps = s;
            if (++s == STB) { s = 0; ph ^= 1; }
        }
        mbar_wait(sempty, 1);
        wg_wait<0>();
        fence_regs(acc4);
        TS(6, threadIdx.x == 0);

        const uint32_t strip = base + STAGING_OFF + c.wg * 16384 + (warp & 3) * 2048;
        const int row0 = m_b * 128 + warp * 16;
#pragma unroll
        for (int h = 0; h < 2; h++) {
#pragma unroll
            for (int q = 0; q < 4; q++) {
                const int i = 32 * h + 8 * q;
                c.stage(4 * h + q, pack_bf16(acc4[i], acc4[i + 1]), pack_bf16(acc4[i + 2], acc4[i + 3]),
                        pack_bf16(acc4[i + 4], acc4[i + 5]), pack_bf16(acc4[i + 6], acc4[i + 7]));
            }
            fence_async_smem();
            __syncwarp();
            if (lane == 0) {
                tma_store_2d(&tm_out, strip + h * 8192, n_b * 128 + h * 64, row0);
                bulk_commit();
            }
        }
        if (lane == 0) asm volatile("cp.async.bulk.wait_group.read 0;" ::: "memory");
        __syncwarp();
        TS(7, threadIdx.x == 0);
        cluster_arrive();
        cluster_wait();
    }
}

typedef CUresult (*EncodeFn)(CUtensorMap*, CUtensorMapDataType, cuuint32_t, void*, const cuuint64_t*, const cuuint64_t*,
                             const cuuint32_t*, const cuuint32_t*, CUtensorMapInterleave, CUtensorMapSwizzle,
                             CUtensorMapL2promotion, CUtensorMapFloatOOBfill);

void map_2d(EncodeFn enc, CUtensorMap* m, const void* p, int rows, int cols, int box_rows) {
    cuuint64_t dims[2] = {(cuuint64_t)cols, (cuuint64_t)rows};
    cuuint64_t str[1] = {(cuuint64_t)cols * 2};
    cuuint32_t box[2] = {64, (cuuint32_t)box_rows};
    cuuint32_t es[2] = {1, 1};
    enc(m, CU_TENSOR_MAP_DATA_TYPE_BFLOAT16, 2, const_cast<void*>(p), dims, str, box, es, CU_TENSOR_MAP_INTERLEAVE_NONE,
        CU_TENSOR_MAP_SWIZZLE_128B, CU_TENSOR_MAP_L2_PROMOTION_L2_128B, CU_TENSOR_MAP_FLOAT_OOB_FILL_NONE);
}
void map_w(EncodeFn enc, CUtensorMap* m, const void* p, int K, int N, int atoms) {
    cuuint64_t dims[3] = {64, (cuuint64_t)K, (cuuint64_t)N / 64};
    cuuint64_t str[2] = {(cuuint64_t)N * 2, 128};
    cuuint32_t box[3] = {64, 64, (cuuint32_t)atoms};
    cuuint32_t es[3] = {1, 1, 1};
    enc(m, CU_TENSOR_MAP_DATA_TYPE_BFLOAT16, 3, const_cast<void*>(p), dims, str, box, es, CU_TENSOR_MAP_INTERLEAVE_NONE,
        CU_TENSOR_MAP_SWIZZLE_128B, CU_TENSOR_MAP_L2_PROMOTION_L2_128B, CU_TENSOR_MAP_FLOAT_OOB_FILL_NONE);
}

}

extern "C" void kernel_launch(void* const* d_in, const int* in_sizes, int n_in, void* d_out, int out_size) {
    (void)in_sizes; (void)n_in; (void)out_size;
    void* fn = nullptr;
    cudaDriverEntryPointQueryResult st;
    cudaGetDriverEntryPoint("cuTensorMapEncodeTiled", &fn, cudaEnableDefault, &st);
    EncodeFn enc = (EncodeFn)fn;
    CUtensorMap x128, x64, g2, u2, g1, u1, d, out;
    map_2d(enc, &x128, d_in[0], M_TOK, D_MODEL, 128);
    map_2d(enc, &x64, d_in[0], M_TOK, D_MODEL, 64);
    map_w(enc, &g2, d_in[1], D_MODEL, D_FF, 2);
    map_w(enc, &u2, d_in[2], D_MODEL, D_FF, 2);
    map_w(enc, &g1, d_in[1], D_MODEL, D_FF, 1);
    map_w(enc, &u1, d_in[2], D_MODEL, D_FF, 1);
    map_w(enc, &d, d_in[3], D_FF, D_MODEL, 2);
    map_2d(enc, &out, d_out, M_TOK, D_MODEL, 16);
    cudaFuncSetAttribute(geglu_ffn_kernel, cudaFuncAttributeMaxDynamicSharedMemorySize, SMEM_BYTES);
    geglu_ffn_kernel<<<NUM_CTAS, NUM_THREADS, SMEM_BYTES>>>(x128, x64, g2, u2, g1, u1, d, out);
}
```

```cpp
#include <cuda_runtime.h>
#include <cuda_bf16.h>
#include <cuda.h>
#include <stdint.h>

namespace {

constexpr int M_TOK = 2048, D_MODEL = 1024, D_FF = 3584;
constexpr int KB_FF = D_FF / 64;
constexpr int NUM_CTAS = 132;
constexpr int NUM_WORK = 128;
constexpr int NUM_THREADS = 384;

constexpr int STA = 4, STA_BYTES = 49152;
constexpr int STB = 6, STB_BYTES = 32768;
constexpr int RING_BYTES = STA * STA_BYTES;
constexpr int STAGING_OFF = RING_BYTES;
constexpr int BAR_OFF = STAGING_OFF + 32768;
#define MAP 0
#define PF 0
constexpr int SMEM_BYTES = BAR_OFF + 256 + 1536 + 1024;

constexpr int BAR_FULL_A = 0, BAR_EMPTY_A = 4, BAR_FULL_B = 8, BAR_EMPTY_B = 14, BAR_SFULL = 20, BAR_SEMPTY = 22, BAR_HREADY = 24;

__device__ __align__(1024) uint8_t g_h[(size_t)M_TOK * D_FF * 2];
__device__ unsigned int g_ready[16 * 4];
__device__ unsigned int g_done;

#define TS(slot, cond)
#define TL(row, idx, cond)
#define TL_DUMP()

__device__ __forceinline__ uint32_t smem_u32(const void* p) { return (uint32_t)__cvta_generic_to_shared(p); }
__device__ __forceinline__ void mbar_init(uint32_t bar, uint32_t cnt) {
    asm volatile("mbarrier.init.shared::cta.b64 [%0], %1;" :: "r"(bar), "r"(cnt) : "memory");
}
__device__ __forceinline__ void mbar_expect_tx(uint32_t bar, uint32_t bytes) {
    asm volatile("mbarrier.arrive.expect_tx.shared::cta.b64 _, [%0], %1;" :: "r"(bar), "r"(bytes) : "memory");
}
__device__ __forceinline__ void mbar_arrive(uint32_t bar) {
    asm volatile("mbarrier.arrive.shared::cta.b64 _, [%0];" :: "r"(bar) : "memory");
}
__device__ __forceinline__ bool mbar_try(uint32_t bar, uint32_t parity) {
    uint32_t done;
    asm volatile("{\n.reg .pred p;\nmbarrier.try_wait.parity.shared::cta.b64 p, [%1], %2;\nselp.u32 %0, 1, 0, p;\n}"
                 : "=r"(done) : "r"(bar), "r"(parity) : "memory");
    return done != 0;
}
__device__ __forceinline__ void mbar_wait_p(uint32_t bar, uint32_t parity) {
    uint32_t it = 0;
    while (!mbar_try(bar, parity)) {
        if (++it > (1u << 20)) __trap();
    }
}
__device__ __forceinline__ void mbar_wait(uint32_t bar, uint32_t parity) {
    if (mbar_try(bar, parity)) return;
    uint32_t it = 0;
    while (!mbar_try(bar, parity)) {
        if (++it > (1u << 21)) break;
    }
}
__device__ __forceinline__ void tma_2d(uint32_t dst, const CUtensorMap* m, uint32_t bar, int c0, int c1) {
    asm volatile("cp.async.bulk.tensor.2d.shared::cluster.global.mbarrier::complete_tx::bytes [%0], [%1, {%3, %4}], [%2];"
                 :: "r"(dst), "l"((uint64_t)m), "r"(bar), "r"(c0), "r"(c1) : "memory");
}
__device__ __forceinline__ void tma_3d(uint32_t dst, const CUtensorMap* m, uint32_t bar, int c0, int c1, int c2) {
    asm volatile("cp.async.bulk.tensor.3d.shared::cluster.global.mbarrier::complete_tx::bytes [%0], [%1, {%3, %4, %5}], [%2];"
                 :: "r"(dst), "l"((uint64_t)m), "r"(bar), "r"(c0), "r"(c1), "r"(c2) : "memory");
}
__device__ __forceinline__ void bulk_load(uint32_t dst, const void* src, uint32_t bytes, uint32_t bar) {
    asm volatile("cp.async.bulk.shared::cluster.global.mbarrier::complete_tx::bytes [%0], [%1], %2, [%3];"
                 :: "r"(dst), "l"(src), "r"(bytes), "r"(bar) : "memory");
}
__device__ __forceinline__ void bulk_store(void* dst, uint32_t src, uint32_t bytes) {
    asm volatile("cp.async.bulk.global.shared::cta.bulk_group [%0], [%1], %2;" :: "l"(dst), "r"(src), "r"(bytes) : "memory");
}
__device__ __forceinline__ void tma_store_2d(const CUtensorMap* m, uint32_t src, int c0, int c1) {
    asm volatile("cp.async.bulk.tensor.2d.global.shared::cta.bulk_group [%0, {%2, %3}], [%1];"
                 :: "l"((uint64_t)m), "r"(src), "r"(c0), "r"(c1) : "memory");
}
__device__ __forceinline__ void prefetch_map(const CUtensorMap* m) {
    asm volatile("prefetch.tensormap [%0];" :: "l"((uint64_t)m) : "memory");
}
__device__ __forceinline__ void bulk_commit() { asm volatile("cp.async.bulk.commit_group;" ::: "memory"); }
__device__ __forceinline__ void fence_async_smem() { asm volatile("fence.proxy.async.shared::cta;" ::: "memory"); }
__device__ __forceinline__ void wg_fence() { asm volatile("wgmma.fence.sync.aligned;" ::: "memory"); }
__device__ __forceinline__ void wg_commit() { asm volatile("wgmma.commit_group.sync.aligned;" ::: "memory"); }
template <int N> __device__ __forceinline__ void wg_wait() { asm volatile("wgmma.wait_group.sync.aligned %0;" :: "n"(N) : "memory"); }

constexpr uint64_t DESC_A_HI = (1ull << 62) | (64ull << 32) | (1ull << 16);
constexpr uint64_t DESC_B_HI = (1ull << 62) | (64ull << 32) | (512ull << 16);
__device__ __forceinline__ uint64_t desc_a(uint32_t addr) { return DESC_A_HI | (uint64_t)((addr & 0x3FFFF) >> 4); }
__device__ __forceinline__ uint64_t desc_b(uint32_t addr) { return DESC_B_HI | (uint64_t)((addr & 0x3FFFF) >> 4); }

#define R8(a, o) "+f"(a[o + 0]), "+f"(a[o + 1]), "+f"(a[o + 2]), "+f"(a[o + 3]), "+f"(a[o + 4]), "+f"(a[o + 5]), "+f"(a[o + 6]), "+f"(a[o + 7])
#define R32(a, o) R8(a, o), R8(a, o + 8), R8(a, o + 16), R8(a, o + 24)

__device__ __forceinline__ void wgmma_n256(float (&d)[128], uint64_t da, uint64_t db, int scale_d) {
    asm volatile("{\n.reg .pred p;\nsetp.ne.b32 p, %130, 0;\n"
        "wgmma.mma_async.sync.aligned.m64n256k16.f32.bf16.bf16 "
        "{%0,%1,%2,%3,%4,%5,%6,%7,%8,%9,%10,%11,%12,%13,%14,%15,%16,%17,%18,%19,%20,%21,%22,%23,%24,%25,%26,%27,%28,%29,%30,%31,"
        "%32,%33,%34,%35,%36,%37,%38,%39,%40,%41,%42,%43,%44,%45,%46,%47,%48,%49,%50,%51,%52,%53,%54,%55,%56,%57,%58,%59,%60,%61,%62,%63,"
        "%64,%65,%66,%67,%68,%69,%70,%71,%72,%73,%74,%75,%76,%77,%78,%79,%80,%81,%82,%83,%84,%85,%86,%87,%88,%89,%90,%91,%92,%93,%94,%95,"
        "%96,%97,%98,%99,%100,%101,%102,%103,%104,%105,%106,%107,%108,%109,%110,%111,%112,%113,%114,%115,%116,%117,%118,%119,%120,%121,%122,%123,%124,%125,%126,%127},"
        " %128, %129, p, 1, 1, 0, 1;\n}\n"
        : R32(d, 0), R32(d, 32), R32(d, 64), R32(d, 96)
        : "l"(da), "l"(db), "r"(scale_d));
}
__device__ __forceinline__ void wgmma_n128(float (&d)[64], uint64_t da, uint64_t db, int scale_d) {
    asm volatile("{\n.reg .pred p;\nsetp.ne.b32 p, %66, 0;\n"
        "wgmma.mma_async.sync.aligned.m64n128k16.f32.bf16.bf16 "
        "{%0,%1,%2,%3,%4,%5,%6,%7,%8,%9,%10,%11,%12,%13,%14,%15,%16,%17,%18,%19,%20,%21,%22,%23,%24,%25,%26,%27,%28,%29,%30,%31,"
        "%32,%33,%34,%35,%36,%37,%38,%39,%40,%41,%42,%43,%44,%45,%46,%47,%48,%49,%50,%51,%52,%53,%54,%55,%56,%57,%58,%59,%60,%61,%62,%63},"
        " %64, %65, p, 1, 1, 0, 1;\n}\n"
        : R32(d, 0), R32(d, 32)
        : "l"(da), "l"(db), "r"(scale_d));
}
template <int N> __device__ __forceinline__ void fence_regs(float (&d)[N]) {
#pragma unroll
    for (int i = 0; i < N; i++) asm volatile("" : "+f"(d[i]) :: "memory");
}

__device__ __forceinline__ uint32_t pack_bf16(float lo, float hi) {
    uint32_t r;
    asm("cvt.rn.bf16x2.f32 %0, %1, %2;" : "=r"(r) : "f"(hi), "f"(lo));
    return r;
}
__device__ __forceinline__ float geglu(float g, float u) {
    const float K0 = -2.3022081986f;
    const float K1 = -0.1029432397f;
    float t = g * fmaf(g * g, K1, K0);
    float e, r;
    asm("ex2.approx.ftz.f32 %0, %1;" : "=f"(e) : "f"(t));
    asm("rcp.approx.ftz.f32 %0, %1;" : "=f"(r) : "f"(1.0f + e));
    return (g * u) * r;
}
__device__ __forceinline__ uint32_t geglu2(uint32_t g, uint32_t u) {
    float lo = geglu(__uint_as_float(g << 16), __uint_as_float(u << 16));
    float hi = geglu(__uint_as_float(g & 0xffff0000u), __uint_as_float(u & 0xffff0000u));
    return pack_bf16(lo, hi);
}
__device__ __forceinline__ void stsm_x4(uint32_t addr, uint32_t r0, uint32_t r1, uint32_t r2, uint32_t r3) {
    asm volatile("stmatrix.sync.aligned.m8n8.x4.shared.b16 [%0], {%1, %2, %3, %4};"
                 :: "r"(addr), "r"(r0), "r"(r1), "r"(r2), "r"(r3) : "memory");
}

struct Consumer {
    uint32_t base;
    uint32_t bars;
    uint32_t st_row;
    uint32_t st_sw;
    uint32_t a_off;
    int lane, wg;
    mutable int tl = 0;

    __device__ __forceinline__ void release(int bar_idx) const {
        if (lane == 0) mbar_arrive(bars + 8 * bar_idx);
    }
    __device__ __forceinline__ void stage(int c, uint32_t r0, uint32_t r1, uint32_t r2, uint32_t r3) const {
        stsm_x4(st_row + (c >> 2) * 8192 + (st_sw ^ ((c & 3) << 5)), r0, r1, r2, r3);
    }
    __device__ __forceinline__ void stage_done() const {
        fence_async_smem();
        __syncwarp();
        if (lane == 0) mbar_arrive(bars + 8 * (BAR_SFULL + wg));
    }
    __device__ __forceinline__ void issue_a(float (&acc)[128], int s, uint32_t parity, bool first) const {
        mbar_wait(bars + 8 * (BAR_FULL_A + s), parity);
        TL(wg, tl++, (threadIdx.x & 127) == 0);
        uint32_t a = base + s * STA_BYTES;
        uint64_t da = desc_a(a + a_off), db = desc_b(a + 16384);
        wg_fence();
        wgmma_n256(acc, da, db, first ? 0 : 1);
        wgmma_n256(acc, da + 2, db + 128, 1);
        wgmma_n256(acc, da + 4, db + 256, 1);
        wgmma_n256(acc, da + 6, db + 384, 1);
        wg_commit();
    }
    __device__ __forceinline__ void issue_b(float (&acc)[64], int s, uint32_t parity, bool first) const {
        mbar_wait(bars + 8 * (BAR_FULL_B + s), parity);
        TL(wg, tl++, (threadIdx.x & 127) == 0);
        uint32_t a = base + s * STB_BYTES;
        uint64_t da = desc_a(a + a_off), db = desc_b(a + 16384);
        wg_fence();
        wgmma_n128(acc, da, db, first ? 0 : 1);
        wgmma_n128(acc, da + 2, db + 128, 1);
        wgmma_n128(acc, da + 4, db + 256, 1);
        wgmma_n128(acc, da + 6, db + 384, 1);
        wg_commit();
    }
};

__global__ void __launch_bounds__(NUM_THREADS, 1)
geglu_ffn_kernel(const __grid_constant__ CUtensorMap tm_x,
                 const __grid_constant__ CUtensorMap tm_g2, const __grid_constant__ CUtensorMap tm_u2,
                 const __grid_constant__ CUtensorMap tm_g1, const __grid_constant__ CUtensorMap tm_u1,
                 const __grid_constant__ CUtensorMap tm_d, const __grid_constant__ CUtensorMap tm_out,
                 const uint8_t* __restrict__ px, const uint8_t* __restrict__ pg, const uint8_t* __restrict__ pu) {
    extern __shared__ uint8_t smem_raw[];
    const uint32_t base = (smem_u32(smem_raw) + 1023) & ~1023u;
    const uint32_t bars = base + BAR_OFF;
    const int warp = __shfl_sync(0xffffffffu, threadIdx.x >> 5, 0);
    const int lane = threadIdx.x & 31;

    uint32_t sm, nsm;
    asm("mov.u32 %0, %%smid;" : "=r"(sm));
    asm("mov.u32 %0, %%nsmid;" : "=r"(nsm));
    if (nsm != NUM_CTAS) sm = blockIdx.x;
    const int tpc = sm >> 1;
    int grp, idx;
    if (tpc < 32) { grp = tpc & 7; idx = tpc >> 3; }
    else if (tpc < 60) { grp = 1 + (tpc - 32) % 7; idx = 4 + (tpc - 32) / 7; }
    else { grp = 0; idx = tpc - 58; }
    if (tpc == 60 || tpc == 61) return;
    const int m_blk = grp * 2 + (sm & 1);
    const int j_blk = idx;

    TL(0, 127, threadIdx.x == 0);
    TS(0, threadIdx.x == 0);
    if (threadIdx.x == 256) {
        for (int s = 0; s < STA; s++) { mbar_init(bars + 8 * (BAR_FULL_A + s), 1); mbar_init(bars + 8 * (BAR_EMPTY_A + s), 8); }
        for (int s = 0; s < STB; s++) { mbar_init(bars + 8 * (BAR_FULL_B + s), 1); mbar_init(bars + 8 * (BAR_EMPTY_B + s), 8); }
        for (int w = 0; w < 2; w++) { mbar_init(bars + 8 * (BAR_SFULL + w), 4); mbar_init(bars + 8 * (BAR_SEMPTY + w), 1); }
        for (int t = 0; t < 4; t++) mbar_init(bars + 8 * (BAR_HREADY + t), 1);
        fence_async_smem();
        for (int s = 0; s < STA; s++) {
            const uint32_t full = bars + 8 * (BAR_FULL_A + s), a = base + s * STA_BYTES;
            TL(2, s, true);
            mbar_expect_tx(full, STA_BYTES);
            tma_2d(a, &tm_x, full, s * 64, m_blk * 128);
            tma_3d(a + 16384, &tm_g2, full, 0, s * 64, j_blk * 2);
            tma_3d(a + 32768, &tm_u2, full, 0, s * 64, j_blk * 2);
        }
    }
    __syncthreads();

    if (warp >= 8) {
        asm volatile("setmaxnreg.dec.sync.aligned.u32 24;");
        if (lane == 0) {
            if (warp == 8) {
                for (int i = STA; i < 48; i++) {
                    const int s = i & 3, kb = i & 15, t = i >> 4;
                    const uint32_t full = bars + 8 * (BAR_FULL_A + s), a = base + s * STA_BYTES;
                    mbar_wait_p(bars + 8 * (BAR_EMPTY_A + s), ((i >> 2) & 1) ^ 1);
                    TL(2, i, true);
                    mbar_expect_tx(full, STA_BYTES);
                    tma_2d(a, &tm_x, full, kb * 64, m_blk * 128);
                    tma_3d(a + 16384, &tm_g2, full, 0, kb * 64, t * 16 + j_blk * 2);
                    tma_3d(a + 32768, &tm_u2, full, 0, kb * 64, t * 16 + j_blk * 2);
                }
                const uint8_t* h_src = g_h + (size_t)m_blk * KB_FF * 16384;
                int s = 0;
                uint32_t ph = 1;
                for (int i = 0; i < 72; i++) {
                    const uint32_t full = bars + 8 * (BAR_FULL_B + s), a = base + s * STB_BYTES;
                    if (i < STB) mbar_wait_p(bars + 8 * (BAR_EMPTY_A + ((2 * i + 1) / 3)), 1);
                    else mbar_wait_p(bars + 8 * (BAR_EMPTY_B + s), ph);
                    TL(2, 48 + i, true);
                    mbar_expect_tx(full, STB_BYTES);
                    if (i < 16) {
                        tma_2d(a, &tm_x, full, i * 64, m_blk * 128);
                        tma_3d(a + 16384, &tm_g1, full, 0, i * 64, 48 + j_blk);
                        tma_3d(a + 24576, &tm_u1, full, 0, i * 64, 48 + j_blk);
                    } else {
                        const int kk = i - 16;
                        tma_3d(a + 16384, &tm_d, full, 0, kk * 64, j_blk * 2);
                        if ((kk & 15) == 0) mbar_wait_p(bars + 8 * (BAR_HREADY + (kk >> 4)), 0);
                        bulk_load(a, h_src + (size_t)kk * 16384, 16384, full);
                    }
                    if (++s == STB) { s = 0; ph ^= 1; }
                }
            } else if (warp <= 10) {
                const int w = warp - 9;
                for (int b = 0; b < 7; b++) {
                    const int t = b >> 1;
                    const int kb = t < 3 ? t * 16 + j_blk * 2 + (b & 1) : 48 + j_blk;
                    uint8_t* dst = g_h + ((size_t)m_blk * KB_FF + kb) * 16384 + w * 8192;
                    const uint32_t src = base + STAGING_OFF + w * 16384 + (b & 1) * 8192;
                    mbar_wait_p(bars + 8 * (BAR_SFULL + w), b & 1);
                    for (int q = 0; q < 4; q++) {
                        bulk_store(dst + q * 2048, src + q * 2048, 2048);
                        bulk_commit();
                        asm volatile("cp.async.bulk.wait_group.read 0;" ::: "memory");
                    }
                    if ((b & 1) || b == 6) {
                        mbar_arrive(bars + 8 * (BAR_SEMPTY + w));
                        asm volatile("cp.async.bulk.wait_group 0;" ::: "memory");
                        asm volatile("fence.proxy.async.global;" ::: "memory");
                        asm volatile("red.release.gpu.global.add.u32 [%0], 1;" :: "l"(g_ready + m_blk * 4 + t) : "memory");
                        if (w == 0) {
                            uint32_t v, it = 0;
                            while (true) {
                                asm volatile("ld.acquire.gpu.global.u32 %0, [%1];" : "=r"(v) : "l"(g_ready + m_blk * 4 + t) : "memory");
                                if (v >= 16) break;
                                if (++it > (1u << 20)) __trap();
                                __nanosleep(200);
                            }
                            asm volatile("fence.proxy.async.global;" ::: "memory");
                            mbar_arrive(bars + 8 * (BAR_HREADY + t));
                        }
                    }
                }
                if (w == 0) {
                    __threadfence();
                    if (atomicAdd(&g_done, 1) == NUM_WORK - 1) {
                        __threadfence();
                        for (int i = 0; i < 16 * 4; i++) g_ready[i] = 0;
                        g_done = 0;
                    }
                }
            } else {
                prefetch_map(&tm_g1);
                prefetch_map(&tm_u1);
                prefetch_map(&tm_d);
                prefetch_map(&tm_out);
            }
        }
    } else {
        asm volatile("setmaxnreg.inc.sync.aligned.u32 240;");
        Consumer c;
        c.base = base;
        c.bars = bars;
        c.lane = lane;
        c.wg = warp >> 2;
        c.a_off = c.wg * 8192;
        c.st_row = base + STAGING_OFF + c.wg * 16384 + ((warp & 3) * 16 + (lane & 15)) * 128;
        c.st_sw = ((lane >> 4) ^ (lane & 7)) << 4;
        const uint32_t sempty = bars + 8 * (BAR_SEMPTY + c.wg);

        float acc[128];
        uint32_t pk[64];
#pragma unroll
        for (int i = 0; i < 64; i++) pk[i] = 0;

#pragma unroll 1
        for (int t = 0; t < 3; t++) {
#pragma unroll
            for (int kb = 0; kb < 8; kb++) {
                c.issue_a(acc, kb & 3, (kb >> 2) & 1, kb == 0);
                TS(1, kb == 0 && t == 0 && threadIdx.x == 0);
                if (kb > 0) { wg_wait<1>(); c.release(BAR_EMPTY_A + ((kb - 1) & 3)); }
                if (t > 0) {
                    if (kb == 0) mbar_wait(sempty, (t & 1));
                    c.stage(kb, geglu2(pk[4 * kb], pk[32 + 4 * kb]), geglu2(pk[4 * kb + 1], pk[33 + 4 * kb]),
                            geglu2(pk[4 * kb + 2], pk[34 + 4 * kb]), geglu2(pk[4 * kb + 3], pk[35 + 4 * kb]));
                    if ((kb & 3) == 3) c.stage_done();
                }
            }
#pragma unroll 1
            for (int kb = 8; kb < 16; kb++) {
                c.issue_a(acc, kb & 3, (kb >> 2) & 1, false);
                wg_wait<1>();
                c.release(BAR_EMPTY_A + ((kb - 1) & 3));
            }
            wg_wait<0>();
            fence_regs(acc);
            c.release(BAR_EMPTY_A + 3);
#pragma unroll
            for (int i = 0; i < 64; i++) pk[i] = pack_bf16(acc[2 * i], acc[2 * i + 1]);
            TS(2 + t, threadIdx.x == 0);
        }

        float acc3[64];
#pragma unroll
        for (int kb = 0; kb < 8; kb++) {
            c.issue_b(acc3, kb % STB, (kb / STB) & 1, kb == 0);
            if (kb > 0) { wg_wait<1>(); c.release(BAR_EMPTY_B + (kb - 1) % STB); }
            if (kb == 0) mbar_wait(sempty, 1);
            c.stage(kb, geglu2(pk[4 * kb], pk[32 + 4 * kb]), geglu2(pk[4 * kb + 1], pk[33 + 4 * kb]),
                    geglu2(pk[4 * kb + 2], pk[34 + 4 * kb]), geglu2(pk[4 * kb + 3], pk[35 + 4 * kb]));
            if ((kb & 3) == 3) c.stage_done();
        }
        int s = 8 % STB, ps = 7 % STB;
        uint32_t ph = (8 / STB) & 1;
#pragma unroll 1
        for (int kb = 8; kb < 16; kb++) {
            c.issue_b(acc3, s, ph, false);
            wg_wait<1>();
            c.release(BAR_EMPTY_B + ps);
            ps = s;
            if (++s == STB) { s = 0; ph ^= 1; }
        }
        TS(5, threadIdx.x == 0);

        float acc4[64];
#pragma unroll
        for (int kb = 0; kb < 4; kb++) {
            c.issue_b(acc4, (16 + kb) % STB, ((16 + kb) / STB) & 1, kb == 0);
            wg_wait<1>();
            c.release(BAR_EMPTY_B + (15 + kb) % STB);
            if (kb == 0) { fence_regs(acc3); mbar_wait(sempty, 0); }
            uint32_t r[4];
#pragma unroll
            for (int q = 0; q < 4; q++) {
                const int i = 8 * kb + 2 * q;
                r[q] = geglu2(pack_bf16(acc3[i], acc3[i + 1]), pack_bf16(acc3[32 + i], acc3[33 + i]));
            }
            c.stage(kb, r[0], r[1], r[2], r[3]);
            if (kb == 3) c.stage_done();
        }
        s = 20 % STB; ps = 19 % STB; ph = (20 / STB) & 1;
#pragma unroll 1
        for (int kb = 4; kb < KB_FF; kb++) {
            c.issue_b(acc4, s, ph, false);
            wg_wait<1>();
            if (kb <= KB_FF - STB) c.release(BAR_EMPTY_B + ps);
            ps = s;
            if (++s == STB) { s = 0; ph ^= 1; }
        }
        mbar_wait(sempty, 1);
        wg_wait<0>();
        fence_regs(acc4);
        TS(6, threadIdx.x == 0);

        const uint32_t strip = base + STAGING_OFF + c.wg * 16384 + (warp & 3) * 2048;
        const int row0 = m_blk * 128 + warp * 16;
#pragma unroll
        for (int h = 0; h < 2; h++) {
#pragma unroll
            for (int q = 0; q < 4; q++) {
                const int i = 32 * h + 8 * q;
                c.stage(4 * h + q, pack_bf16(acc4[i], acc4[i + 1]), pack_bf16(acc4[i + 2], acc4[i + 3]),
                        pack_bf16(acc4[i + 4], acc4[i + 5]), pack_bf16(acc4[i + 6], acc4[i + 7]));
            }
            fence_async_smem();
            __syncwarp();
            if (lane == 0) {
                tma_store_2d(&tm_out, strip + h * 8192, j_blk * 128 + h * 64, row0);
                bulk_commit();
            }
        }
        if (lane == 0) asm volatile("cp.async.bulk.wait_group.read 0;" ::: "memory");
        __syncwarp();
        TS(7, threadIdx.x == 0);
        TL_DUMP();
    }
}

typedef CUresult (*EncodeFn)(CUtensorMap*, CUtensorMapDataType, cuuint32_t, void*, const cuuint64_t*, const cuuint64_t*,
                             const cuuint32_t*, const cuuint32_t*, CUtensorMapInterleave, CUtensorMapSwizzle,
                             CUtensorMapL2promotion, CUtensorMapFloatOOBfill);

void map_2d(EncodeFn enc, CUtensorMap* m, const void* p, int rows, int cols, int box_rows) {
    cuuint64_t dims[2] = {(cuuint64_t)cols, (cuuint64_t)rows};
    cuuint64_t str[1] = {(cuuint64_t)cols * 2};
    cuuint32_t box[2] = {64, (cuuint32_t)box_rows};
    cuuint32_t es[2] = {1, 1};
    enc(m, CU_TENSOR_MAP_DATA_TYPE_BFLOAT16, 2, const_cast<void*>(p), dims, str, box, es, CU_TENSOR_MAP_INTERLEAVE_NONE,
        CU_TENSOR_MAP_SWIZZLE_128B, CU_TENSOR_MAP_L2_PROMOTION_L2_128B, CU_TENSOR_MAP_FLOAT_OOB_FILL_NONE);
}
void map_w(EncodeFn enc, CUtensorMap* m, const void* p, int K, int N, int atoms) {
    cuuint64_t dims[3] = {64, (cuuint64_t)K, (cuuint64_t)N / 64};
    cuuint64_t str[2] = {(cuuint64_t)N * 2, 128};
    cuuint32_t box[3] = {64, 64, (cuuint32_t)atoms};
    cuuint32_t es[3] = {1, 1, 1};
    enc(m, CU_TENSOR_MAP_DATA_TYPE_BFLOAT16, 3, const_cast<void*>(p), dims, str, box, es, CU_TENSOR_MAP_INTERLEAVE_NONE,
        CU_TENSOR_MAP_SWIZZLE_128B, CU_TENSOR_MAP_L2_PROMOTION_L2_128B, CU_TENSOR_MAP_FLOAT_OOB_FILL_NONE);
}

}

extern "C" void kernel_launch(void* const* d_in, const int* in_sizes, int n_in, void* d_out, int out_size) {
    (void)in_sizes; (void)n_in; (void)out_size;
    void* fn = nullptr;
    cudaDriverEntryPointQueryResult st;
    cudaGetDriverEntryPoint("cuTensorMapEncodeTiled", &fn, cudaEnableDefault, &st);
    EncodeFn enc = (EncodeFn)fn;
    CUtensorMap x128, g2, u2, g1, u1, d, out;
    map_2d(enc, &x128, d_in[0], M_TOK, D_MODEL, 128);
    map_w(enc, &g2, d_in[1], D_MODEL, D_FF, 2);
    map_w(enc, &u2, d_in[2], D_MODEL, D_FF, 2);
    map_w(enc, &g1, d_in[1], D_MODEL, D_FF, 1);
    map_w(enc, &u1, d_in[2], D_MODEL, D_FF, 1);
    map_w(enc, &d, d_in[3], D_FF, D_MODEL, 2);
    map_2d(enc, &out, d_out, M_TOK, D_MODEL, 16);
    cudaFuncSetAttribute(geglu_ffn_kernel, cudaFuncAttributeMaxDynamicSharedMemorySize, SMEM_BYTES);
    geglu_ffn_kernel<<<NUM_CTAS, NUM_THREADS, SMEM_BYTES>>>(x128, g2, u2, g1, u1, d, out, (const uint8_t*)d_in[0],
                                                            (const uint8_t*)d_in[1], (const uint8_t*)d_in[2]);
}
```

```cpp
#include <cuda_runtime.h>
#include <cuda_bf16.h>
#include <cuda.h>
#include <stdint.h>

namespace {

constexpr int M_TOK = 2048, D_MODEL = 1024, D_FF = 3584;
constexpr int KB_FF = D_FF / 64;
constexpr int NUM_CTAS = 132;
constexpr int NUM_WORK = 128;
constexpr int NUM_THREADS = 384;

constexpr int STA = 4, STA_BYTES = 49152;
constexpr int STB = 6, STB_BYTES = 32768;
constexpr int RING_BYTES = STA * STA_BYTES;
constexpr int STAGING_OFF = RING_BYTES;
constexpr int BAR_OFF = STAGING_OFF + 32768;
#define PAIR 1
#define MAP 0
constexpr int SMEM_BYTES = BAR_OFF + 256 + 1536;
constexpr uint32_t base = 1024, bars = base + BAR_OFF;

constexpr int BAR_FULL_A = 0, BAR_EMPTY_A = 4, BAR_FULL_B = 8, BAR_EMPTY_B = 14, BAR_SFULL = 20, BAR_SEMPTY = 22,
              BAR_HREADY = 26, BAR_FULL_U0 = 30;

__device__ __align__(1024) uint8_t g_h[(size_t)M_TOK * D_FF * 2];
__device__ unsigned int g_ready[16 * 4];
__device__ unsigned int g_done;

#define TS(slot, cond)
#define TL(row, idx, cond)
#define TL_DUMP()

__device__ __forceinline__ uint32_t smem_u32(const void* p) { return (uint32_t)__cvta_generic_to_shared(p); }
__device__ __forceinline__ bool elect_one() {
    uint32_t p;
    asm volatile("{\n.reg .pred p;\nelect.sync _|p, 0xffffffff;\nselp.u32 %0, 1, 0, p;\n}" : "=r"(p));
    return p != 0;
}
__device__ __forceinline__ void mbar_init(uint32_t bar, uint32_t cnt) {
    asm volatile("mbarrier.init.shared::cta.b64 [%0], %1;" :: "r"(bar), "r"(cnt) : "memory");
}
__device__ __forceinline__ void mbar_expect_tx(uint32_t bar, uint32_t bytes) {
    asm volatile("mbarrier.arrive.expect_tx.shared::cta.b64 _, [%0], %1;" :: "r"(bar), "r"(bytes) : "memory");
}
__device__ __forceinline__ void mbar_arrive(uint32_t bar) {
    asm volatile("mbarrier.arrive.shared::cta.b64 _, [%0];" :: "r"(bar) : "memory");
}
__device__ __forceinline__ bool mbar_try(uint32_t bar, uint32_t parity) {
    uint32_t done;
    asm volatile("{\n.reg .pred p;\nmbarrier.try_wait.parity.shared::cta.b64 p, [%1], %2;\nselp.u32 %0, 1, 0, p;\n}"
                 : "=r"(done) : "r"(bar), "r"(parity) : "memory");
    return done != 0;
}
__device__ __forceinline__ void mbar_wait_p(uint32_t bar, uint32_t parity) {
    uint32_t it = 0;
#pragma unroll 1
    while (!mbar_try(bar, parity)) {
        if (++it > (1u << 20)) __trap();
    }
}
__device__ __forceinline__ void mbar_wait(uint32_t bar, uint32_t parity) {
    if (mbar_try(bar, parity)) return;
    uint32_t it = 0;
#pragma unroll 1
    while (!mbar_try(bar, parity)) {
        if (++it > (1u << 21)) break;
    }
}
__device__ __forceinline__ void tma_2d(uint32_t dst, const CUtensorMap* m, uint32_t bar, int c0, int c1) {
    asm volatile("cp.async.bulk.tensor.2d.shared::cluster.global.mbarrier::complete_tx::bytes [%0], [%1, {%3, %4}], [%2];"
                 :: "r"(dst), "l"((uint64_t)m), "r"(bar), "r"(c0), "r"(c1) : "memory");
}
__device__ __forceinline__ void tma_3d(uint32_t dst, const CUtensorMap* m, uint32_t bar, int c0, int c1, int c2) {
    asm volatile("cp.async.bulk.tensor.3d.shared::cluster.global.mbarrier::complete_tx::bytes [%0], [%1, {%3, %4, %5}], [%2];"
                 :: "r"(dst), "l"((uint64_t)m), "r"(bar), "r"(c0), "r"(c1), "r"(c2) : "memory");
}
__device__ __forceinline__ void bulk_load(uint32_t dst, const void* src, uint32_t bytes, uint32_t bar) {
    asm volatile("cp.async.bulk.shared::cluster.global.mbarrier::complete_tx::bytes [%0], [%1], %2, [%3];"
                 :: "r"(dst), "l"(src), "r"(bytes), "r"(bar) : "memory");
}
__device__ __forceinline__ void bulk_store(void* dst, uint32_t src, uint32_t bytes) {
    asm volatile("cp.async.bulk.global.shared::cta.bulk_group [%0], [%1], %2;" :: "l"(dst), "r"(src), "r"(bytes) : "memory");
}
__device__ __forceinline__ void tma_store_2d(const CUtensorMap* m, uint32_t src, int c0, int c1) {
    asm volatile("cp.async.bulk.tensor.2d.global.shared::cta.bulk_group [%0, {%2, %3}], [%1];"
                 :: "l"((uint64_t)m), "r"(src), "r"(c0), "r"(c1) : "memory");
}
__device__ __forceinline__ void prefetch_map(const CUtensorMap* m) {
    asm volatile("prefetch.tensormap [%0];" :: "l"((uint64_t)m) : "memory");
}
__device__ __forceinline__ void bulk_commit() { asm volatile("cp.async.bulk.commit_group;" ::: "memory"); }
__device__ __forceinline__ void fence_async_smem() { asm volatile("fence.proxy.async.shared::cta;" ::: "memory"); }
__device__ __forceinline__ void wg_fence() { asm volatile("wgmma.fence.sync.aligned;" ::: "memory"); }
__device__ __forceinline__ void wg_commit() { asm volatile("wgmma.commit_group.sync.aligned;" ::: "memory"); }
template <int N> __device__ __forceinline__ void wg_wait() { asm volatile("wgmma.wait_group.sync.aligned %0;" :: "n"(N) : "memory"); }

constexpr uint64_t DESC_A_HI = (1ull << 62) | (64ull << 32) | (1ull << 16);
constexpr uint64_t DESC_B_HI = (1ull << 62) | (64ull << 32) | (512ull << 16);
constexpr uint64_t DESC_BH_HI = (1ull << 62) | (64ull << 32) | (256ull << 16);
__device__ __forceinline__ uint64_t desc_a(uint32_t addr) { return DESC_A_HI | (uint64_t)(addr >> 4); }
__device__ __forceinline__ uint64_t desc_b(uint32_t addr) { return DESC_B_HI | (uint64_t)(addr >> 4); }

#define R8(a, o) "+f"(a[o + 0]), "+f"(a[o + 1]), "+f"(a[o + 2]), "+f"(a[o + 3]), "+f"(a[o + 4]), "+f"(a[o + 5]), "+f"(a[o + 6]), "+f"(a[o + 7])
#define R32(a, o) R8(a, o), R8(a, o + 8), R8(a, o + 16), R8(a, o + 24)

__device__ __forceinline__ void wgmma_n256(float (&d)[128], uint64_t da, uint64_t db, int scale_d) {
    asm volatile("{\n.reg .pred p;\nsetp.ne.b32 p, %130, 0;\n"
        "wgmma.mma_async.sync.aligned.m64n256k16.f32.bf16.bf16 "
        "{%0,%1,%2,%3,%4,%5,%6,%7,%8,%9,%10,%11,%12,%13,%14,%15,%16,%17,%18,%19,%20,%21,%22,%23,%24,%25,%26,%27,%28,%29,%30,%31,"
        "%32,%33,%34,%35,%36,%37,%38,%39,%40,%41,%42,%43,%44,%45,%46,%47,%48,%49,%50,%51,%52,%53,%54,%55,%56,%57,%58,%59,%60,%61,%62,%63,"
        "%64,%65,%66,%67,%68,%69,%70,%71,%72,%73,%74,%75,%76,%77,%78,%79,%80,%81,%82,%83,%84,%85,%86,%87,%88,%89,%90,%91,%92,%93,%94,%95,"
        "%96,%97,%98,%99,%100,%101,%102,%103,%104,%105,%106,%107,%108,%109,%110,%111,%112,%113,%114,%115,%116,%117,%118,%119,%120,%121,%122,%123,%124,%125,%126,%127},"
        " %128, %129, p, 1, 1, 0, 1;\n}\n"
        : R32(d, 0), R32(d, 32), R32(d, 64), R32(d, 96)
        : "l"(da), "l"(db), "r"(scale_d));
}
template <int O, int N>
__device__ __forceinline__ void wgmma_n128(float (&d)[N], uint64_t da, uint64_t db, int scale_d) {
    asm volatile("{\n.reg .pred p;\nsetp.ne.b32 p, %66, 0;\n"
        "wgmma.mma_async.sync.aligned.m64n128k16.f32.bf16.bf16 "
        "{%0,%1,%2,%3,%4,%5,%6,%7,%8,%9,%10,%11,%12,%13,%14,%15,%16,%17,%18,%19,%20,%21,%22,%23,%24,%25,%26,%27,%28,%29,%30,%31,"
        "%32,%33,%34,%35,%36,%37,%38,%39,%40,%41,%42,%43,%44,%45,%46,%47,%48,%49,%50,%51,%52,%53,%54,%55,%56,%57,%58,%59,%60,%61,%62,%63},"
        " %64, %65, p, 1, 1, 0, 1;\n}\n"
        : R32(d, O), R32(d, O + 32)
        : "l"(da), "l"(db), "r"(scale_d));
}
template <int N> __device__ __forceinline__ void fence_regs(float (&d)[N]) {
#pragma unroll
    for (int i = 0; i < N; i++) asm volatile("" : "+f"(d[i]) :: "memory");
}

__device__ __forceinline__ uint32_t pack_bf16(float lo, float hi) {
    uint32_t r;
    asm("cvt.rn.bf16x2.f32 %0, %1, %2;" : "=r"(r) : "f"(hi), "f"(lo));
    return r;
}
__device__ __forceinline__ float geglu(float g, float u) {
    const float K0 = -2.3022081986f;
    const float K1 = -0.1029432397f;
    float t = g * fmaf(g * g, K1, K0);
    float e, r;
    asm("ex2.approx.ftz.f32 %0, %1;" : "=f"(e) : "f"(t));
    asm("rcp.approx.ftz.f32 %0, %1;" : "=f"(r) : "f"(1.0f + e));
    return (g * u) * r;
}
__device__ __forceinline__ uint32_t geglu2(uint32_t g, uint32_t u) {
    float lo = geglu(__uint_as_float(g << 16), __uint_as_float(u << 16));
    float hi = geglu(__uint_as_float(g & 0xffff0000u), __uint_as_float(u & 0xffff0000u));
    return pack_bf16(lo, hi);
}
__device__ __forceinline__ void stsm_x4(uint32_t addr, uint32_t r0, uint32_t r1, uint32_t r2, uint32_t r3) {
    asm volatile("stmatrix.sync.aligned.m8n8.x4.shared.b16 [%0], {%1, %2, %3, %4};"
                 :: "r"(addr), "r"(r0), "r"(r1), "r"(r2), "r"(r3) : "memory");
}

__device__ __forceinline__ void stsm_x2(uint32_t addr, uint32_t r0, uint32_t r1) {
    asm volatile("stmatrix.sync.aligned.m8n8.x2.shared.b16 [%0], {%1, %2};" :: "r"(addr), "r"(r0), "r"(r1) : "memory");
}

struct Consumer {
    uint32_t st_row;
    uint32_t st_sw;
    uint32_t a_off;
    int lane, wg;
    mutable int tl = 0;

    __device__ __forceinline__ void release(int bar_idx) const {
        if (lane == 0) mbar_arrive(bars + 8 * bar_idx);
    }
    __device__ __forceinline__ void stage(int c, uint32_t r0, uint32_t r1, uint32_t r2, uint32_t r3) const {
        stsm_x4(st_row + (c >> 2) * 8192 + (st_sw ^ ((c & 3) << 5)), r0, r1, r2, r3);
    }
    template <int N>
    __device__ __forceinline__ void stage_half(int h, const float (&v)[N], int g, int u) const {
        stsm_x2(st_row + (h >> 3) * 8192 + (((h & 7) ^ (lane & 7)) << 4),
                pack_bf16(geglu(v[g], v[u]), geglu(v[g + 1], v[u + 1])), pack_bf16(geglu(v[g + 2], v[u + 2]), geglu(v[g + 3], v[u + 3])));
    }
    __device__ __forceinline__ void stage_done() const {
        fence_async_smem();
        __syncwarp();
        if (lane == 0) mbar_arrive(bars + 8 * (BAR_SFULL + wg));
    }
    __device__ __forceinline__ void wait_full(int bar_idx, uint32_t parity) const {
        mbar_wait(bars + 8 * bar_idx, parity);
    }
    __device__ __forceinline__ void mma_n256(float (&acc)[128], uint32_t a, bool first = false, bool very_first = false) const {
        TL(wg, tl++, (threadIdx.x & 127) == 0);
        uint64_t da = desc_a(a + a_off), db = DESC_BH_HI | (uint64_t)((a + 16384) >> 4);
        wg_fence();
        wgmma_n256(acc, da, db, first ? 0 : 1);
        wgmma_n256(acc, da + 2, db + 128, 1);
        if (very_first) wait_full(BAR_FULL_U0, 0);
        if (first) wg_fence();
        wgmma_n256(acc, da + 4, db + 1024, 1);
        wgmma_n256(acc, da + 6, db + 1152, 1);
        wg_commit();
    }
    template <int O, int N>
    __device__ __forceinline__ void mma_n128(float (&acc)[N], uint32_t a, uint32_t b, bool first) const {
        TL(wg, tl++, O == 0 && (threadIdx.x & 127) == 0);
        uint64_t da = desc_a(a + a_off), db = desc_b(b);
        wg_fence();
        wgmma_n128<O>(acc, da, db, first ? 0 : 1);
        wgmma_n128<O>(acc, da + 2, db + 128, 1);
        wgmma_n128<O>(acc, da + 4, db + 256, 1);
        wgmma_n128<O>(acc, da + 6, db + 384, 1);
        wg_commit();
    }
};

__global__ void __launch_bounds__(NUM_THREADS, 1)
geglu_ffn_kernel(const __grid_constant__ CUtensorMap tm_x,
                 const __grid_constant__ CUtensorMap tm_g2, const __grid_constant__ CUtensorMap tm_u2,
                 const __grid_constant__ CUtensorMap tm_g1, const __grid_constant__ CUtensorMap tm_u1,
                 const __grid_constant__ CUtensorMap tm_d, const __grid_constant__ CUtensorMap tm_out) {
    extern __shared__ __align__(1024) uint8_t smem_raw[];
    const int warp = __shfl_sync(0xffffffffu, threadIdx.x >> 5, 0);
    const int lane = threadIdx.x & 31;

    uint32_t sm, nsm;
    asm("mov.u32 %0, %%smid;" : "=r"(sm));
    asm("mov.u32 %0, %%nsmid;" : "=r"(nsm));
    if (nsm != NUM_CTAS) sm = blockIdx.x;
    const int tpc = sm >> 1;
    int grp, idx;
    if (tpc < 32) { grp = tpc & 7; idx = tpc >> 3; }
    else if (tpc < 60) { grp = 1 + (tpc - 32) % 7; idx = 4 + (tpc - 32) / 7; }
    else { grp = 0; idx = tpc - 58; }
    if (tpc == 60 || tpc == 61) return;
    const int m_blk = grp * 2 + (sm & 1);
    const int j_blk = idx;

    TL(0, 127, threadIdx.x == 0);
    TS(0, threadIdx.x == 352);
    if (warp >= 8) {
        asm volatile("setmaxnreg.dec.sync.aligned.u32 24;");
        TL(2, 123, threadIdx.x == 256);
        if (elect_one()) {
            if (warp == 8) {
                const uint32_t full = bars + 8 * BAR_FULL_A, full_u = bars + 8 * BAR_FULL_U0;
                mbar_init(full, 1);
                mbar_init(full_u, 1);
                fence_async_smem();
                TL(2, 0, true);
                mbar_expect_tx(full, 32768);
                tma_2d(base, &tm_x, full, 0, m_blk * 128);
                tma_3d(base + 16384, &tm_g2, full, 0, 0, j_blk * 2);
                tma_3d(base + 24576, &tm_u2, full, 0, 0, j_blk * 2);
                mbar_expect_tx(full_u, 16384);
                tma_3d(base + 32768, &tm_g2, full_u, 0, 32, j_blk * 2);
                tma_3d(base + 40960, &tm_u2, full_u, 0, 32, j_blk * 2);
                TL(2, 121, true);
            } else if (warp == 9) {
#pragma unroll
                for (int i = 1; i < BAR_FULL_U0; i++) {
                    const bool empty = (i >= BAR_EMPTY_A && i < BAR_FULL_B) || (i >= BAR_EMPTY_B && i < BAR_SFULL);
                    mbar_init(bars + 8 * i, empty ? 8 : (i == BAR_SFULL || i == BAR_SFULL + 1) ? 4 : 1);
                }
                fence_async_smem();
            }
        }
        __syncwarp();
        asm volatile("bar.arrive 1, 384;" ::: "memory");
        asm volatile("bar.sync 2, 128;" ::: "memory");
        if (elect_one()) {
            if (warp == 8) {
                for (int i = 1; i < 48; i++) {
                    const int s = i & 3, kb = i & 15, t = i >> 4;
                    const uint32_t full = bars + 8 * (BAR_FULL_A + s), a = base + s * STA_BYTES;
                    mbar_wait_p(bars + 8 * (BAR_EMPTY_A + s), ((i >> 2) & 1) ^ 1);
                    TL(2, i, true);
                    mbar_expect_tx(full, STA_BYTES);
                    tma_2d(a, &tm_x, full, kb * 64, m_blk * 128);
                    tma_3d(a + 16384, &tm_g2, full, 0, kb * 64, t * 16 + j_blk * 2);
                    tma_3d(a + 24576, &tm_u2, full, 0, kb * 64, t * 16 + j_blk * 2);
                    tma_3d(a + 32768, &tm_g2, full, 0, kb * 64 + 32, t * 16 + j_blk * 2);
                    tma_3d(a + 40960, &tm_u2, full, 0, kb * 64 + 32, t * 16 + j_blk * 2);
                }
                const uint8_t* h_src = g_h + (size_t)m_blk * KB_FF * 16384;
                int s = 0;
                uint32_t ph = 1;
                for (int i = 0; i < 72; i++) {
                    const uint32_t full = bars + 8 * (BAR_FULL_B + s), a = base + s * STB_BYTES;
                    if (i < STB) mbar_wait_p(bars + 8 * (BAR_EMPTY_A + ((2 * i + 1) / 3)), 1);
                    else mbar_wait_p(bars + 8 * (BAR_EMPTY_B + s), ph);
                    TL(2, 48 + i, true);
                    mbar_expect_tx(full, STB_BYTES);
                    if (i < 16) {
                        tma_2d(a, &tm_x, full, i * 64, m_blk * 128);
                        tma_3d(a + 16384, &tm_g1, full, 0, i * 64, 48 + j_blk);
                        tma_3d(a + 24576, &tm_u1, full, 0, i * 64, 48 + j_blk);
                    } else {
                        const int kk = i - 16;
                        tma_3d(a + 16384, &tm_d, full, 0, kk * 64, j_blk * 2);
                        if ((kk & 15) == 0) mbar_wait_p(bars + 8 * (BAR_HREADY + (kk >> 4)), 0);
                        bulk_load(a, h_src + (size_t)kk * 16384, 16384, full);
                    }
                    if (++s == STB) { s = 0; ph ^= 1; }
                }
            } else if (warp <= 10) {
                const int w = warp - 9;
                for (int b = 0; b < 7; b++) {
                    const int t = b >> 1;
                    const int kb = t < 3 ? t * 16 + j_blk * 2 + (b & 1) : 48 + j_blk;
                    uint8_t* dst = g_h + ((size_t)m_blk * KB_FF + kb) * 16384 + w * 8192;
                    const uint32_t src = base + STAGING_OFF + w * 16384 + (b & 1) * 8192;
                    mbar_wait_p(bars + 8 * (BAR_SFULL + w), b & 1);
                    for (int q = 0; q < 4; q++) {
                        bulk_store(dst + q * 2048, src + q * 2048, 2048);
                        bulk_commit();
                        asm volatile("cp.async.bulk.wait_group.read 0;" ::: "memory");
                    }
                    mbar_arrive(bars + 8 * (BAR_SEMPTY + 2 * w + (b & 1)));
                    if ((b & 1) || b == 6) {
                        asm volatile("cp.async.bulk.wait_group 0;" ::: "memory");
                        asm volatile("fence.proxy.async.global;" ::: "memory");
                        asm volatile("red.release.gpu.global.add.u32 [%0], 1;" :: "l"(g_ready + m_blk * 4 + t) : "memory");
                        if (w == 0) {
                            uint32_t v, it = 0;
                            while (true) {
                                asm volatile("ld.acquire.gpu.global.u32 %0, [%1];" : "=r"(v) : "l"(g_ready + m_blk * 4 + t) : "memory");
                                if (v >= 16) break;
                                if (++it > (1u << 20)) __trap();
                                __nanosleep(200);
                            }
                            asm volatile("fence.proxy.async.global;" ::: "memory");
                            mbar_arrive(bars + 8 * (BAR_HREADY + t));
                        }
                    }
                }
                if (w == 0) {
                    __threadfence();
                    if (atomicAdd(&g_done, 1) == NUM_WORK - 1) {
                        __threadfence();
#pragma unroll 1
                        for (int i = 0; i < 16 * 4; i++) g_ready[i] = 0;
                        g_done = 0;
                    }
                }
            } else {
                if (smem_u32(smem_raw) != base) __trap();
                prefetch_map(&tm_g1);
                prefetch_map(&tm_u1);
                prefetch_map(&tm_d);
                prefetch_map(&tm_out);
            }
        }
    } else {
        TL(0, 121, threadIdx.x == 0);
        asm volatile("setmaxnreg.inc.sync.aligned.u32 240;");
        TL(0, 123, threadIdx.x == 0);
        asm volatile("bar.sync 1, 384;" ::: "memory");
        TL(0, 122, threadIdx.x == 0);
        Consumer c;
        c.lane = lane;
        c.wg = warp >> 2;
        c.a_off = c.wg * 8192;
        c.st_row = base + STAGING_OFF + c.wg * 16384 + ((warp & 3) * 16 + (lane & 15)) * 128;
        c.st_sw = ((lane >> 4) ^ (lane & 7)) << 4;
        const uint32_t sempty = bars + 8 * (BAR_SEMPTY + 2 * c.wg);

        float acc[128];
        uint32_t pk[64];
#pragma unroll
        for (int i = 0; i < 64; i++) asm volatile("" : "=r"(pk[i]));
#pragma unroll
        for (int i = 0; i < 128; i++) asm volatile("" : "=f"(acc[i]));

        const bool always = nsm != 0;

        c.wait_full(BAR_FULL_A, 0);
        TL(0, 124, threadIdx.x == 0);
#pragma unroll 1
        for (int t = 0;; t++) {
            c.mma_n256(acc, base, true, t == 0);
            TS(1, t == 0 && threadIdx.x == 0);
            c.wait_full(BAR_FULL_A + 1, 0);
#pragma unroll
            for (int kb = 1; kb < 9; kb++) {
                if (kb > 1 || !PAIR) wg_wait<0>();
                c.mma_n256(acc, base + (kb & 3) * STA_BYTES);
                if (kb == 1 && PAIR) wg_wait<1>();
                c.release(BAR_EMPTY_A + ((kb - 1) & 3));
                if (t > 0) {
                    const int q = 4 * (kb - 1);
                    if ((kb & 3) == 1) mbar_wait(sempty + 8 * (kb >> 2), t & 1);
                    c.stage(kb - 1, geglu2(pk[q], pk[32 + q]), geglu2(pk[q + 1], pk[33 + q]),
                            geglu2(pk[q + 2], pk[34 + q]), geglu2(pk[q + 3], pk[35 + q]));
                    if ((kb & 3) == 0) c.stage_done();
                }
                c.wait_full(BAR_FULL_A + ((kb + 1) & 3), ((kb + 1) >> 2) & 1);
            }
#pragma unroll 1
            for (int kb = 9; kb < 15; kb++) {
                wg_wait<0>();
                c.mma_n256(acc, base + (kb & 3) * STA_BYTES);
                c.release(BAR_EMPTY_A + ((kb - 1) & 3));
                c.wait_full(BAR_FULL_A + ((kb + 1) & 3), ((kb + 1) >> 2) & 1);
            }
            if (!PAIR || t == 2) wg_wait<0>();
            c.mma_n256(acc, base + 3 * STA_BYTES);
            wg_wait<1>();
            c.release(BAR_EMPTY_A + 2);
            c.wait_full(t == 2 ? BAR_FULL_B : BAR_FULL_A, 0);
            wg_wait<0>();
            fence_regs(acc);
            if (t == 2) break;
            c.release(BAR_EMPTY_A + 3);
#pragma unroll
            for (int i = 0; i < 64; i++) pk[i] = pack_bf16(acc[2 * i], acc[2 * i + 1]);
            TS(2 + t, threadIdx.x == 0);
        }

        float acc3[64];
#pragma unroll
        for (int kb = 0; kb < 16; kb++) {
            const uint32_t a = base + (kb % STB) * STB_BYTES;
            if (kb > 0) wg_wait<0>();
            c.mma_n128<0>(acc3, a, a + 16384, kb == 0);
            c.release(kb == 0 ? BAR_EMPTY_A + 3 : BAR_EMPTY_B + (kb - 1) % STB);
            if (always) {
                if ((kb & 7) == 0) mbar_wait(sempty + (kb & 8), 1);
                c.stage_half(kb, acc, 4 * kb, 64 + 4 * kb);
                if ((kb & 7) == 7) c.stage_done();
            }
            c.wait_full(BAR_FULL_B + (kb + 1) % STB, ((kb + 1) / STB) & 1);
        }
        TS(5, threadIdx.x == 0);

        float acc4[64];
#pragma unroll
        for (int kb = 0; kb < 8; kb++) {
            const uint32_t a = base + ((16 + kb) % STB) * STB_BYTES;
            wg_wait<0>();
            if (kb == 0) fence_regs(acc3);
            c.mma_n128<0>(acc4, a, a + 16384, kb == 0);
            c.release(BAR_EMPTY_B + (15 + kb) % STB);
            if (always) {
                if (kb == 0) mbar_wait(sempty, 0);
                c.stage_half(kb, acc3, 4 * kb, 32 + 4 * kb);
                if (kb == 7) c.stage_done();
            }
            c.wait_full(BAR_FULL_B + (17 + kb) % STB, ((17 + kb) / STB) & 1);
        }
        int s = 24 % STB, ps = 23 % STB;
        uint32_t ph = (24 / STB) & 1;
#pragma unroll 1
        for (int kb = 8; kb < KB_FF; kb++) {
            const uint32_t a = base + s * STB_BYTES;
            wg_wait<0>();
            c.mma_n128<0>(acc4, a, a + 16384, false);
            c.release(BAR_EMPTY_B + ps);
            ps = s;
            if (++s == STB) { s = 0; ph ^= 1; }
            if (kb < KB_FF - 1) c.wait_full(BAR_FULL_B + s, ph);
        }
        mbar_wait(sempty, 1);
        mbar_wait(sempty + 8, 0);
        wg_wait<0>();
        fence_regs(acc4);
        TS(6, threadIdx.x == 0);
        TL(c.wg, 125, (threadIdx.x & 127) == 0);

        const uint32_t strip = base + STAGING_OFF + c.wg * 16384 + (warp & 3) * 2048;
        const int row0 = m_blk * 128 + warp * 16;
#pragma unroll
        for (int h = 0; h < 2; h++) {
#pragma unroll
            for (int q = 0; q < 4; q++) {
                const int i = 32 * h + 8 * q;
                c.stage(4 * h + q, pack_bf16(acc4[i], acc4[i + 1]), pack_bf16(acc4[i + 2], acc4[i + 3]),
                        pack_bf16(acc4[i + 4], acc4[i + 5]), pack_bf16(acc4[i + 6], acc4[i + 7]));
            }
            fence_async_smem();
            __syncwarp();
            if (elect_one()) {
                tma_store_2d(&tm_out, strip + h * 8192, j_blk * 128 + h * 64, row0);
                bulk_commit();
            }
        }
        if (elect_one()) asm volatile("cp.async.bulk.wait_group.read 0;" ::: "memory");
        __syncwarp();
        TL(c.wg, 126, (threadIdx.x & 127) == 0);
        TS(7, threadIdx.x == 0);
        TL_DUMP();
    }
}

typedef CUresult (*EncodeFn)(CUtensorMap*, CUtensorMapDataType, cuuint32_t, void*, const cuuint64_t*, const cuuint64_t*,
                             const cuuint32_t*, const cuuint32_t*, CUtensorMapInterleave, CUtensorMapSwizzle,
                             CUtensorMapL2promotion, CUtensorMapFloatOOBfill);

void map_2d(EncodeFn enc, CUtensorMap* m, const void* p, int rows, int cols, int box_rows) {
    cuuint64_t dims[2] = {(cuuint64_t)cols, (cuuint64_t)rows};
    cuuint64_t str[1] = {(cuuint64_t)cols * 2};
    cuuint32_t box[2] = {64, (cuuint32_t)box_rows};
    cuuint32_t es[2] = {1, 1};
    enc(m, CU_TENSOR_MAP_DATA_TYPE_BFLOAT16, 2, const_cast<void*>(p), dims, str, box, es, CU_TENSOR_MAP_INTERLEAVE_NONE,
        CU_TENSOR_MAP_SWIZZLE_128B, CU_TENSOR_MAP_L2_PROMOTION_L2_128B, CU_TENSOR_MAP_FLOAT_OOB_FILL_NONE);
}
void map_w(EncodeFn enc, CUtensorMap* m, const void* p, int K, int N, int rows, int atoms) {
    cuuint64_t dims[3] = {64, (cuuint64_t)K, (cuuint64_t)N / 64};
    cuuint64_t str[2] = {(cuuint64_t)N * 2, 128};
    cuuint32_t box[3] = {64, (cuuint32_t)rows, (cuuint32_t)atoms};
    cuuint32_t es[3] = {1, 1, 1};
    enc(m, CU_TENSOR_MAP_DATA_TYPE_BFLOAT16, 3, const_cast<void*>(p), dims, str, box, es, CU_TENSOR_MAP_INTERLEAVE_NONE,
        CU_TENSOR_MAP_SWIZZLE_128B, CU_TENSOR_MAP_L2_PROMOTION_L2_128B, CU_TENSOR_MAP_FLOAT_OOB_FILL_NONE);
}

}

extern "C" void kernel_launch(void* const* d_in, const int* in_sizes, int n_in, void* d_out, int out_size) {
    (void)in_sizes; (void)n_in; (void)out_size;
    void* fn = nullptr;
    cudaDriverEntryPointQueryResult st;
    cudaGetDriverEntryPoint("cuTensorMapEncodeTiled", &fn, cudaEnableDefault, &st);
    EncodeFn enc = (EncodeFn)fn;
    CUtensorMap x128, g2, u2, g1, u1, d, out;
    map_2d(enc, &x128, d_in[0], M_TOK, D_MODEL, 128);
    map_w(enc, &g2, d_in[1], D_MODEL, D_FF, 32, 2);
    map_w(enc, &u2, d_in[2], D_MODEL, D_FF, 32, 2);
    map_w(enc, &g1, d_in[1], D_MODEL, D_FF, 64, 1);
    map_w(enc, &u1, d_in[2], D_MODEL, D_FF, 64, 1);
    map_w(enc, &d, d_in[3], D_FF, D_MODEL, 64, 2);
    map_2d(enc, &out, d_out, M_TOK, D_MODEL, 16);
    cudaFuncSetAttribute(geglu_ffn_kernel, cudaFuncAttributeMaxDynamicSharedMemorySize, SMEM_BYTES);
    geglu_ffn_kernel<<<NUM_CTAS, NUM_THREADS, SMEM_BYTES>>>(x128, g2, u2, g1, u1, d, out);
}
```

```cpp
#include <cuda_runtime.h>
#include <cuda_bf16.h>
#include <cuda.h>
#include <stdint.h>

namespace {

constexpr int M_TOK = 2048, D_MODEL = 1024, D_FF = 3584;
constexpr int KB_FF = D_FF / 64;
constexpr int NUM_CTAS = 132;
constexpr int NUM_WORK = 128;
constexpr int NUM_THREADS = 384;

constexpr int STA = 4, STC = 5, STB = 6;
constexpr int W_OFF = STA * 16384;
constexpr int RING_BYTES = 196608;
constexpr int STAGING_OFF = RING_BYTES;
constexpr int BAR_OFF = STAGING_OFF + 32768;
#define SMR 1
constexpr int SMEM_BYTES = BAR_OFF + 512 + 1536;
constexpr uint32_t base = 1024, bars = base + BAR_OFF;

constexpr int BAR_FULL_A = 0, BAR_EMPTY_A = 4, BAR_FULL_B = 8, BAR_EMPTY_B = 14, BAR_SFULL = 20, BAR_SEMPTY = 24,
              BAR_HREADY = 28, BAR_FULL_C = 32, BAR_PIECE = 37;

__device__ __align__(1024) uint8_t g_h[(size_t)M_TOK * D_FF * 2];
__device__ __align__(16) unsigned int g_ready[16 * 4];

#define TS(slot, cond)
#define TL(row, idx, cond)
#define TL_DUMP()

__device__ __forceinline__ uint32_t smem_u32(const void* p) { return (uint32_t)__cvta_generic_to_shared(p); }
__device__ __forceinline__ bool elect_one() {
    uint32_t p;
    asm volatile("{\n.reg .pred p;\nelect.sync _|p, 0xffffffff;\nselp.u32 %0, 1, 0, p;\n}" : "=r"(p));
    return p != 0;
}
__device__ __forceinline__ void mbar_init(uint32_t bar, uint32_t cnt) {
    asm volatile("mbarrier.init.shared::cta.b64 [%0], %1;" :: "r"(bar), "r"(cnt) : "memory");
}
__device__ __forceinline__ void mbar_expect_tx(uint32_t bar, uint32_t bytes) {
    asm volatile("mbarrier.arrive.expect_tx.shared::cta.b64 _, [%0], %1;" :: "r"(bar), "r"(bytes) : "memory");
}
__device__ __forceinline__ void mbar_arrive(uint32_t bar) {
    asm volatile("mbarrier.arrive.shared::cta.b64 _, [%0];" :: "r"(bar) : "memory");
}
__device__ __forceinline__ bool mbar_try(uint32_t bar, uint32_t parity) {
    uint32_t done;
    asm volatile("{\n.reg .pred p;\nmbarrier.try_wait.parity.shared::cta.b64 p, [%1], %2;\nselp.u32 %0, 1, 0, p;\n}"
                 : "=r"(done) : "r"(bar), "r"(parity) : "memory");
    return done != 0;
}
__device__ __forceinline__ void mbar_wait_p(uint32_t bar, uint32_t parity) {
    uint32_t it = 0;
#pragma unroll 1
    while (!mbar_try(bar, parity)) {
        if (++it > (1u << 20)) __trap();
    }
}
__device__ __forceinline__ void mbar_wait(uint32_t bar, uint32_t parity) {
    if (mbar_try(bar, parity)) return;
    uint32_t it = 0;
#pragma unroll 1
    while (!mbar_try(bar, parity)) {
        if (++it > (1u << 21)) break;
    }
}
__device__ __forceinline__ void tma_2d(uint32_t dst, const CUtensorMap* m, uint32_t bar, int c0, int c1) {
    asm volatile("cp.async.bulk.tensor.2d.shared::cluster.global.mbarrier::complete_tx::bytes [%0], [%1, {%3, %4}], [%2];"
                 :: "r"(dst), "l"((uint64_t)m), "r"(bar), "r"(c0), "r"(c1) : "memory");
}
__device__ __forceinline__ void tma_3d(uint32_t dst, const CUtensorMap* m, uint32_t bar, int c0, int c1, int c2) {
    asm volatile("cp.async.bulk.tensor.3d.shared::cluster.global.mbarrier::complete_tx::bytes [%0], [%1, {%3, %4, %5}], [%2];"
                 :: "r"(dst), "l"((uint64_t)m), "r"(bar), "r"(c0), "r"(c1), "r"(c2) : "memory");
}
__device__ __forceinline__ void bulk_load(uint32_t dst, const void* src, uint32_t bytes, uint32_t bar) {
    asm volatile("cp.async.bulk.shared::cluster.global.mbarrier::complete_tx::bytes [%0], [%1], %2, [%3];"
                 :: "r"(dst), "l"(src), "r"(bytes), "r"(bar) : "memory");
}
__device__ __forceinline__ void bulk_store(void* dst, uint32_t src, uint32_t bytes) {
    asm volatile("cp.async.bulk.global.shared::cta.bulk_group [%0], [%1], %2;" :: "l"(dst), "r"(src), "r"(bytes) : "memory");
}
__device__ __forceinline__ void tma_store_2d(const CUtensorMap* m, uint32_t src, int c0, int c1) {
    asm volatile("cp.async.bulk.tensor.2d.global.shared::cta.bulk_group [%0, {%2, %3}], [%1];"
                 :: "l"((uint64_t)m), "r"(src), "r"(c0), "r"(c1) : "memory");
}
__device__ __forceinline__ void prefetch_map(const CUtensorMap* m) {
    asm volatile("prefetch.tensormap [%0];" :: "l"((uint64_t)m) : "memory");
}
__device__ __forceinline__ void prefetch_l2(const void* p, uint32_t bytes) {
    asm volatile("cp.async.bulk.prefetch.L2.global [%0], %1;" :: "l"(p), "r"(bytes) : "memory");
}
__device__ __forceinline__ void bulk_commit() { asm volatile("cp.async.bulk.commit_group;" ::: "memory"); }
__device__ __forceinline__ void fence_async_smem() { asm volatile("fence.proxy.async.shared::cta;" ::: "memory"); }
__device__ __forceinline__ void wg_fence() { asm volatile("wgmma.fence.sync.aligned;" ::: "memory"); }
__device__ __forceinline__ void wg_commit() { asm volatile("wgmma.commit_group.sync.aligned;" ::: "memory"); }
template <int N> __device__ __forceinline__ void wg_wait() { asm volatile("wgmma.wait_group.sync.aligned %0;" :: "n"(N) : "memory"); }

constexpr uint32_t HI_SW = (1u << 30) | 64u, HI_H = 16u;
__host__ __device__ constexpr uint32_t desc_lo(uint32_t addr, uint32_t lbo) { return (addr >> 4) | ((lbo >> 4) << 16); }

#define R8(a, o) "+f"(a[o + 0]), "+f"(a[o + 1]), "+f"(a[o + 2]), "+f"(a[o + 3]), "+f"(a[o + 4]), "+f"(a[o + 5]), "+f"(a[o + 6]), "+f"(a[o + 7])
#define R32(a, o) R8(a, o), R8(a, o + 8), R8(a, o + 16), R8(a, o + 24)

template <uint32_t HA, int O = 0, int N>
__device__ __forceinline__ void wgmma_n256(float (&d)[N], uint32_t da, uint32_t db, int scale_d) {
    asm volatile("{\n.reg .pred p;\n.reg .b64 da, db;\nsetp.ne.b32 p, %130, 0;\nmov.b64 da, {%128, %131};\nmov.b64 db, {%129, %132};\n"
        "wgmma.mma_async.sync.aligned.m64n256k16.f32.bf16.bf16 "
        "{%0,%1,%2,%3,%4,%5,%6,%7,%8,%9,%10,%11,%12,%13,%14,%15,%16,%17,%18,%19,%20,%21,%22,%23,%24,%25,%26,%27,%28,%29,%30,%31,"
        "%32,%33,%34,%35,%36,%37,%38,%39,%40,%41,%42,%43,%44,%45,%46,%47,%48,%49,%50,%51,%52,%53,%54,%55,%56,%57,%58,%59,%60,%61,%62,%63,"
        "%64,%65,%66,%67,%68,%69,%70,%71,%72,%73,%74,%75,%76,%77,%78,%79,%80,%81,%82,%83,%84,%85,%86,%87,%88,%89,%90,%91,%92,%93,%94,%95,"
        "%96,%97,%98,%99,%100,%101,%102,%103,%104,%105,%106,%107,%108,%109,%110,%111,%112,%113,%114,%115,%116,%117,%118,%119,%120,%121,%122,%123,%124,%125,%126,%127},"
        " da, db, p, 1, 1, 0, 1;\n}\n"
        : R32(d, O + 0), R32(d, O + 32), R32(d, O + 64), R32(d, O + 96)
        : "r"(da), "r"(db), "r"(scale_d), "n"(HA), "n"(HI_SW));
}
template <uint32_t HA, int O = 0, int N>
__device__ __forceinline__ void wgmma_n176(float (&d)[N], uint32_t da, uint32_t db, int scale_d) {
    asm volatile("{\n.reg .pred p;\n.reg .b64 da, db;\nsetp.ne.b32 p, %90, 0;\nmov.b64 da, {%88, %91};\nmov.b64 db, {%89, %92};\n"
        "wgmma.mma_async.sync.aligned.m64n176k16.f32.bf16.bf16 "
        "{%0,%1,%2,%3,%4,%5,%6,%7,%8,%9,%10,%11,%12,%13,%14,%15,%16,%17,%18,%19,%20,%21,%22,%23,%24,%25,%26,%27,%28,%29,%30,%31,"
        "%32,%33,%34,%35,%36,%37,%38,%39,%40,%41,%42,%43,%44,%45,%46,%47,%48,%49,%50,%51,%52,%53,%54,%55,%56,%57,%58,%59,%60,%61,%62,%63,"
        "%64,%65,%66,%67,%68,%69,%70,%71,%72,%73,%74,%75,%76,%77,%78,%79,%80,%81,%82,%83,%84,%85,%86,%87},"
        " da, db, p, 1, 1, 0, 1;\n}\n"
        : R32(d, O + 0), R32(d, O + 32), R8(d, O + 64), R8(d, O + 72), R8(d, O + 80)
        : "r"(da), "r"(db), "r"(scale_d), "n"(HA), "n"(HI_SW));
}
template <uint32_t HA, int O = 0, int N>
__device__ __forceinline__ void wgmma_n128(float (&d)[N], uint32_t da, uint32_t db, int scale_d) {
    asm volatile("{\n.reg .pred p;\n.reg .b64 da, db;\nsetp.ne.b32 p, %66, 0;\nmov.b64 da, {%64, %67};\nmov.b64 db, {%65, %68};\n"
        "wgmma.mma_async.sync.aligned.m64n128k16.f32.bf16.bf16 "
        "{%0,%1,%2,%3,%4,%5,%6,%7,%8,%9,%10,%11,%12,%13,%14,%15,%16,%17,%18,%19,%20,%21,%22,%23,%24,%25,%26,%27,%28,%29,%30,%31,"
        "%32,%33,%34,%35,%36,%37,%38,%39,%40,%41,%42,%43,%44,%45,%46,%47,%48,%49,%50,%51,%52,%53,%54,%55,%56,%57,%58,%59,%60,%61,%62,%63},"
        " da, db, p, 1, 1, 0, 1;\n}\n"
        : R32(d, O + 0), R32(d, O + 32)
        : "r"(da), "r"(db), "r"(scale_d), "n"(HA), "n"(HI_SW));
}
template <int M, int N> __device__ __forceinline__ void fence_regs(float (&d)[N]) {
#pragma unroll
    for (int i = 0; i < M; i++) asm volatile("" : "+f"(d[i]) :: "memory");
}

__device__ __forceinline__ uint32_t pack_bf16(float lo, float hi) {
    uint32_t r;
    asm("cvt.rn.bf16x2.f32 %0, %1, %2;" : "=r"(r) : "f"(hi), "f"(lo));
    return r;
}
__device__ __forceinline__ float gelu_gate(float g) {
    const float K0 = -2.3022081986f;
    const float K1 = -0.1029432397f;
    float t = g * fmaf(g * g, K1, K0);
    float e, r;
    asm("ex2.approx.ftz.f32 %0, %1;" : "=f"(e) : "f"(t));
    asm("rcp.approx.ftz.f32 %0, %1;" : "=f"(r) : "f"(1.0f + e));
    return r;
}
__device__ __forceinline__ float geglu(float g, float u) { return (g * u) * gelu_gate(g); }
__device__ __forceinline__ uint32_t gelu2(float lo, float hi) { return pack_bf16(lo * gelu_gate(lo), hi * gelu_gate(hi)); }
__device__ __forceinline__ uint32_t mul_bf16x2(uint32_t a, uint32_t b) {
    uint32_t r;
    asm("mul.rn.bf16x2 %0, %1, %2;" : "=r"(r) : "r"(a), "r"(b));
    return r;
}
__device__ __forceinline__ uint32_t geglu2(uint32_t g, uint32_t u) {
    float lo = geglu(__uint_as_float(g << 16), __uint_as_float(u << 16));
    float hi = geglu(__uint_as_float(g & 0xffff0000u), __uint_as_float(u & 0xffff0000u));
    return pack_bf16(lo, hi);
}
__device__ __forceinline__ void stsm_x4(uint32_t addr, uint32_t r0, uint32_t r1, uint32_t r2, uint32_t r3) {
    asm volatile("stmatrix.sync.aligned.m8n8.x4.shared.b16 [%0], {%1, %2, %3, %4};"
                 :: "r"(addr), "r"(r0), "r"(r1), "r"(r2), "r"(r3) : "memory");
}

#define PF 15
#define PACE0 300
#define PACE1 800
#define PACE2 0
#define POLL 200
#define EXP 0
struct Maps { CUtensorMap x64, g16, u16, w32[2], x128, w64[2], part[2], d, out; const uint8_t *wg, *wu, *wd; };

struct Consumer {
    uint32_t st_h;
    int lane, wg;
    mutable int tl = 0;

    __device__ __forceinline__ void release(int bar_idx) const {
        if (lane == 0) mbar_arrive(bars + 8 * bar_idx);
    }
    __device__ __forceinline__ void wait_full(int bar_idx, uint32_t parity) const { mbar_wait(bars + 8 * bar_idx, parity); }
    __device__ __forceinline__ void stage(int c, uint32_t parity, bool last, uint32_t r0, uint32_t r1, uint32_t r2, uint32_t r3) const {
        if ((c & 3) == 0) mbar_wait(bars + 8 * (BAR_SEMPTY + 2 * wg + ((c >> 2) & 1)), parity);
        stsm_x4(st_h + (c & 7) * 2048, r0, r1, r2, r3);
        if (last) {
            fence_async_smem();
            __syncwarp();
            if (lane == 0) mbar_arrive(bars + 8 * (BAR_SFULL + 2 * wg + ((c >> 2) & 1)));
        }
    }
    __device__ __forceinline__ void stage_geglu(int c, uint32_t parity, const uint32_t (&pk)[64]) const {
        const int q = 4 * c;
        stage(c, parity, (c & 3) == 3, geglu2(pk[q], pk[32 + q]), geglu2(pk[q + 1], pk[33 + q]),
              geglu2(pk[q + 2], pk[34 + q]), geglu2(pk[q + 3], pk[35 + q]));
    }
    __device__ __forceinline__ void mma_a(float (&acc)[128], int s, bool first = false) const {
        TL(wg, tl++, (threadIdx.x & 127) == 0);
        const uint32_t da = desc_lo(base, 16) + s * 1024 + wg * 512, db = desc_lo(base + W_OFF, 4096) + s * 2048;
        wg_fence();
        wgmma_n256<HI_SW>(acc, da, db, first ? 0 : 1);
        wgmma_n256<HI_SW>(acc, da + 2, db + 128, 1);
        wgmma_n256<HI_SW>(acc, da + 4, db + 1024, 1);
        wgmma_n256<HI_SW>(acc, da + 6, db + 1152, 1);
        wg_commit();
    }
    template <int N>
    __device__ __forceinline__ void mma_c(float (&acc)[N], int s, int ws, bool first = false) const {
        TL(wg, tl++, (threadIdx.x & 127) == 0);
        const uint32_t da = desc_lo(base, 16) + s * 1024 + wg * 512, db = desc_lo(base + W_OFF, 8192) + ws * 1536;
        wg_fence();
        wgmma_n176<HI_SW>(acc, da, db, first ? 0 : 1);
        wgmma_n176<HI_SW>(acc, da + 2, db + 128, 1);
        wgmma_n176<HI_SW>(acc, da + 4, db + 256, 1);
        wgmma_n176<HI_SW>(acc, da + 6, db + 384, 1);
        wg_commit();
    }
    __device__ __forceinline__ void mma_b(float (&acc)[64], int s, int ps, bool first = false) const {
        TL(wg, tl++, (threadIdx.x & 127) == 0);
        const uint32_t da = desc_lo(base + 16384, 128) + ps * 2048 + wg * 128, db = desc_lo(base, 8192) + s * 2048;
        wg_fence();
        wgmma_n128<HI_H>(acc, da, db, first ? 0 : 1);
        wgmma_n128<HI_H>(acc, da + 256, db + 128, 1);
        wgmma_n128<HI_H>(acc, da + 512, db + 256, 1);
        wgmma_n128<HI_H>(acc, da + 768, db + 384, 1);
        wg_commit();
    }
    __device__ __forceinline__ void step_a(float (&acc)[128], int kb) const {
        mma_a(acc, kb & 3);
        release(BAR_EMPTY_A + ((kb - 1) & 3));
    }
    __device__ __forceinline__ void next_a(int kb) const { wait_full(BAR_FULL_A + ((kb + 1) & 3), ((kb + 1) >> 2) & 1); }
    template <int N>
    __device__ __forceinline__ void step_c(float (&acc)[N], int kb, int ws, bool first = false) const {
        mma_c(acc, kb & 3, ws, first);
        release(BAR_EMPTY_A + ((kb - 1) & 3));
    }
    __device__ __forceinline__ void next_c(int kb) const { wait_full(BAR_FULL_C + (kb + 1) % STC, ((kb + 1) / STC) & 1); }
};

__global__ void __launch_bounds__(NUM_THREADS, 1) geglu_ffn_kernel(const __grid_constant__ Maps mp) {
    extern __shared__ __align__(1024) uint8_t smem_raw[];
    const int warp = __shfl_sync(0xffffffffu, threadIdx.x >> 5, 0);
    const int lane = threadIdx.x & 31;

    uint32_t sm;
    asm("mov.u32 %0, %%smid;" : "=r"(sm));
    const int tpc = sm >> 1;
    const int q7 = ((tpc - 32) * 37) >> 8;
    const bool extra = (tpc >> 1) == 30;
    const int grp = tpc < 32 ? tpc & 7 : tpc < 60 ? tpc - 31 - 7 * q7 : 0;
    const int j_blk = tpc < 32 ? tpc >> 3 : tpc < 60 ? 4 + q7 : tpc - 58;
    const int m_blk = extra ? (sm & 3) * 4 : grp * 2 + (sm & 1);
    const int col0 = extra ? 54 : j_blk * 2;

    const uint32_t full0 = bars + 8 * BAR_FULL_A, piece = bars + 8 * BAR_PIECE;
    if (warp == 8) {
        if (elect_one()) {
            mbar_init(full0, 1);
            mbar_init(piece, 1);
            mbar_init(piece + 8, 1);
            mbar_init(piece + 16, 1);
            asm volatile("fence.mbarrier_init.release.cluster;" ::: "memory");
            TL(2, 0, true);
            mbar_expect_tx(full0, 16384);
            tma_2d(base, &mp.x64, full0, 0, m_blk * 128);
            tma_3d(base + W_OFF, &mp.g16, full0, 0, 0, col0);
            tma_3d(base + W_OFF + 4096, &mp.u16, full0, 0, 0, col0);
            mbar_expect_tx(piece, 8192);
            tma_2d(base + 8192, &mp.x64, piece, 0, m_blk * 128 + 64);
            mbar_expect_tx(piece + 8, 8192);
            tma_3d(base + W_OFF + 8192, &mp.g16, piece + 8, 0, 16, col0);
            tma_3d(base + W_OFF + 12288, &mp.u16, piece + 8, 0, 16, col0);
            mbar_expect_tx(piece + 16, 16384);
            tma_3d(base + W_OFF + 16384, &mp.w32[0], piece + 16, 0, 32, col0);
            tma_3d(base + W_OFF + 24576, &mp.w32[1], piece + 16, 0, 32, col0);
            TL(2, 121, true);
            mbar_init(full0 + 8, 1);
            mbar_init(full0 + 16, 1);
            mbar_init(full0 + 24, 1);
            mbar_init(piece + 24, 1);
            asm volatile("fence.mbarrier_init.release.cluster;" ::: "memory");
        }
        __syncwarp();
        asm volatile("bar.arrive 4, 384;" ::: "memory");
    } else {
        asm volatile("bar.sync 4, 384;" ::: "memory");
        asm volatile("nanosleep.u32 0;" ::: "memory");
    }

    if (warp < 8) {
        TL(0, 121, threadIdx.x == 0);
        if (warp == 0) {
            if (elect_one()) {
#pragma unroll
                for (int i = BAR_EMPTY_A; i < BAR_PIECE; i++) {
                    const bool empty = (i >= BAR_EMPTY_A && i < BAR_FULL_B) || (i >= BAR_EMPTY_B && i < BAR_SFULL);
                    mbar_init(bars + 8 * i, empty ? 8 : (i >= BAR_SFULL && i < BAR_SEMPTY) ? 4 : 1);
                }
                asm volatile("fence.mbarrier_init.release.cluster;" ::: "memory");
            }
            __syncwarp();
            asm volatile("bar.arrive 2, 160;" ::: "memory");
        }
        asm volatile("setmaxnreg.inc.sync.aligned.u32 240;");
        TL(0, 123, threadIdx.x == 0);
        asm volatile("bar.sync 1, 256;" ::: "memory");
        TL(0, 122, threadIdx.x == 0);
        Consumer c;
        c.lane = lane;
        c.wg = warp >> 2;
        c.st_h = base + STAGING_OFF + c.wg * 16384 + (warp & 3) * 512 + (lane & 8) * 32 + (lane >> 4) * 128 + (lane & 7) * 16;
        const bool always = sm != 0xffffffffu;

        float acc[128];
        uint32_t pk[64];
#pragma unroll
        for (int i = 0; i < 64; i++) asm volatile("" : "=r"(pk[i]));
#pragma unroll
        for (int i = 0; i < 128; i++) asm volatile("" : "=f"(acc[i]));

        {
            const uint32_t da = desc_lo(base, 16) + c.wg * 512, da1 = da + 1024;
            constexpr uint32_t dq = desc_lo(base + W_OFF, 2048), dh = desc_lo(base + W_OFF, 4096), dh1 = dh + 2048;
            c.wait_full(c.wg ? BAR_PIECE : BAR_FULL_A, 0);
            c.wait_full(BAR_FULL_A, 0);
            TL(0, 124, threadIdx.x == 0);
            TL(c.wg, c.tl++, (threadIdx.x & 127) == 0);
            wg_fence();
            wgmma_n256<HI_SW>(acc, da, dq, 0);
            TS(1, threadIdx.x == 0);
            c.wait_full(BAR_PIECE + 1, 0);
            wg_fence();
            wgmma_n256<HI_SW>(acc, da + 2, dq + 512, 1);
            c.wait_full(BAR_PIECE + 2, 0);
            wg_fence();
            wgmma_n256<HI_SW>(acc, da + 4, dh + 1024, 1);
            wgmma_n256<HI_SW>(acc, da + 6, dh + 1152, 1);
            wg_commit();
            c.wait_full(BAR_FULL_A + 1, 0);
            TL(c.wg, c.tl++, (threadIdx.x & 127) == 0);
            wg_fence();
            wgmma_n256<HI_SW>(acc, da1, dh1, 1);
            wgmma_n256<HI_SW>(acc, da1 + 2, dh1 + 128, 1);
            c.wait_full(BAR_PIECE + 3, 0);
            wg_fence();
            wgmma_n256<HI_SW>(acc, da1 + 4, dh1 + 1024, 1);
            wgmma_n256<HI_SW>(acc, da1 + 6, dh1 + 1152, 1);
            wg_commit();
            wg_wait<1>();
            c.release(BAR_EMPTY_A);
            c.wait_full(BAR_FULL_A + 2, 0);
        }

        const int last = extra ? 3 : 1;
#pragma unroll 1
        for (int t = 0;; t++) {
#pragma unroll
            for (int kb = 2; kb < 10; kb++) {
                wg_wait<0>();
                c.step_a(acc, kb);
                if (t > 0) c.stage_geglu(kb - 2, t & 1, pk);
                c.next_a(kb);
            }
#pragma unroll 1
            for (int kb = 10; kb < 15; kb++) {
                wg_wait<0>();
                c.step_a(acc, kb);
                c.next_a(kb);
            }
            c.mma_a(acc, 3);
            wg_wait<1>();
            c.release(BAR_EMPTY_A + 2);
            if (t < 3) c.wait_full(t == last ? BAR_FULL_C : BAR_FULL_A, 0);
            wg_wait<0>();
            fence_regs<128>(acc);
            c.release(BAR_EMPTY_A + 3);
#pragma unroll
            for (int i = 0; i < 64; i++) pk[i] = pack_bf16(acc[2 * i], acc[2 * i + 1]);
            TS(2 + t, threadIdx.x == 0);
            if (t == last) break;
            c.mma_a(acc, 0, true);
            c.wait_full(BAR_FULL_A + 1, 0);
            c.mma_a(acc, 1);
            wg_wait<1>();
            c.release(BAR_EMPTY_A);
            c.wait_full(BAR_FULL_A + 2, 0);
        }
        if (extra) {
#pragma unroll
            for (int q = 0; q < 8; q++) c.stage_geglu(q, 0, pk);
            TS(7, threadIdx.x == 0);
            TL(c.wg, 126, (threadIdx.x & 127) == 0);
            TL_DUMP();
            return;
        }

        c.mma_c(acc, 0, 0, true);
        c.next_c(0);
        c.mma_c(acc, 1, 1);
        wg_wait<1>();
        c.release(BAR_EMPTY_A);
        c.next_c(1);
#pragma unroll
        for (int kb = 2; kb < 10; kb++) {
            wg_wait<0>();
            c.step_c(acc, kb, kb % STC);
            if (always) c.stage_geglu(kb - 2, 0, pk);
            c.next_c(kb);
        }
#pragma unroll 1
        for (int kb = 10; kb < 16; kb++) {
            wg_wait<0>();
            c.step_c(acc, kb, kb < 15 ? kb - 10 : 0);
            c.wait_full(BAR_FULL_C + (kb < 14 ? kb - 9 : kb - 14), kb >= 14);
        }
        TS(4, threadIdx.x == 0);

        float acc3[88];
        uint32_t gp[44];
#pragma unroll
        for (int kb = 0; kb < 11; kb++) {
            wg_wait<0>();
            if (kb == 0) fence_regs<88>(acc);
            c.step_c(acc3, kb, (16 + kb) % STC, kb == 0);
#pragma unroll
            for (int i = 40 - 4 * kb; i < 44 - 4 * kb; i++) asm volatile("" : "=r"(gp[i]));
            if (always) {
#pragma unroll
                for (int i = 40 - 4 * kb; i < 44 - 4 * kb; i++) {
                    gp[i] = gelu2(acc[2 * i], acc[2 * i + 1]);
                    asm volatile("" : "+r"(gp[i]));
                }
            }
            c.next_c(16 + kb);
        }
#pragma unroll 1
        for (int kb = 11; kb < 16; kb++) {
            wg_wait<0>();
            c.step_c(acc3, kb, kb < 14 ? kb - 9 : kb - 14);
            c.wait_full(kb < 13 ? BAR_FULL_C + kb - 8 : kb < 15 ? BAR_FULL_C + kb - 13 : BAR_FULL_B + 4, kb < 13);
        }
        TS(5, threadIdx.x == 0);

        float acc4[64];
#pragma unroll
        for (int kb = 0; kb < 11; kb++) {
            wg_wait<0>();
            if (kb == 0) fence_regs<88>(acc3);
            c.mma_b(acc4, (kb + 4) % STB, (kb + 3) % STB, kb == 0);
            c.release(kb == 0 ? BAR_EMPTY_A + 3 : BAR_EMPTY_B + (kb + 3) % STB);
            if (always) {
                const int q = 4 * kb, r = 8 * kb;
                c.stage(kb, kb < 8, (kb & 3) == 3 || kb == 10,
                        mul_bf16x2(gp[q], pack_bf16(acc3[r], acc3[r + 1])), mul_bf16x2(gp[q + 1], pack_bf16(acc3[r + 2], acc3[r + 3])),
                        mul_bf16x2(gp[q + 2], pack_bf16(acc3[r + 4], acc3[r + 5])), mul_bf16x2(gp[q + 3], pack_bf16(acc3[r + 6], acc3[r + 7])));
            }
            c.wait_full(BAR_FULL_B + (kb + 5) % STB, ((kb + 1) / STB) & 1);
        }
        int s = 15 % STB, ps = 14 % STB;
        uint32_t ph = (11 / STB) & 1;
#pragma unroll 1
        for (int kb = 11; kb < KB_FF; kb++) {
            wg_wait<0>();
            c.mma_b(acc4, s, ps);
            c.release(BAR_EMPTY_B + ps);
            ps = s;
            if (++s == STB) s = 0;
            if (s == 4) ph ^= 1;
            if (kb < KB_FF - 1) c.wait_full(BAR_FULL_B + s, ph);
        }
        c.wait_full(BAR_SEMPTY + 2 * c.wg, 1);
        c.wait_full(BAR_SEMPTY + 2 * c.wg + 1, 0);
        const uint32_t strip = base + STAGING_OFF + c.wg * 16384 + (warp & 3) * 2048;
        const uint32_t st_row = strip + (lane & 15) * 128, st_sw = ((lane >> 4) ^ (lane & 7)) << 4;
        const int row0 = m_blk * 128 + warp * 16;
        wg_wait<0>();
        fence_regs<64>(acc4);
        TS(6, threadIdx.x == 0);
        TL(c.wg, 125, (threadIdx.x & 127) == 0);

#pragma unroll
        for (int h = 0; h < 2; h++) {
#pragma unroll
            for (int q = 0; q < 4; q++) {
                const int i = 32 * h + 8 * q;
                stsm_x4(st_row + h * 8192 + (st_sw ^ (q << 5)), pack_bf16(acc4[i], acc4[i + 1]), pack_bf16(acc4[i + 2], acc4[i + 3]),
                        pack_bf16(acc4[i + 4], acc4[i + 5]), pack_bf16(acc4[i + 6], acc4[i + 7]));
            }
            fence_async_smem();
            __syncwarp();
            if (elect_one()) {
                tma_store_2d(&mp.out, strip + h * 8192, j_blk * 128 + h * 64, row0);
                bulk_commit();
            }
        }
        if (elect_one()) asm volatile("cp.async.bulk.wait_group.read 0;" ::: "memory");
        __syncwarp();
        TL(c.wg, 126, (threadIdx.x & 127) == 0);
        TS(7, threadIdx.x == 0);
        TL_DUMP();
    } else {
        asm volatile("setmaxnreg.dec.sync.aligned.u32 24;");
        if (warp == 8 && elect_one()) {
#pragma unroll 1
            for (int i = 1; i < STA; i++) {
                const uint32_t f = full0 + 8 * i, f2 = i == 1 ? piece + 24 : f, b = base + W_OFF + i * 32768;
                TL(2, i, true);
                mbar_expect_tx(f, i == 1 ? 32768 : 49152);
                if (i == 1) mbar_expect_tx(f2, 16384);
                tma_2d(base + i * 16384, &mp.x128, f, i * 64, m_blk * 128);
                tma_3d(b, &mp.w32[0], f, 0, i * 64, col0);
                tma_3d(b + 8192, &mp.w32[1], f, 0, i * 64, col0);
                tma_3d(b + 16384, &mp.w32[0], f2, 0, i * 64 + 32, col0);
                tma_3d(b + 24576, &mp.w32[1], f2, 0, i * 64 + 32, col0);
            }
        }
        __syncwarp();
        asm volatile("bar.sync 2, 160;" ::: "memory");
        uint32_t cnt[4];
        if (warp == 11)
            asm volatile("ld.relaxed.gpu.global.v4.u32 {%0, %1, %2, %3}, [%4];"
                         : "=r"(cnt[0]), "=r"(cnt[1]), "=r"(cnt[2]), "=r"(cnt[3]) : "l"(g_ready + m_blk * 4) : "memory");
        if (warp > 8) asm volatile("bar.sync 5, 96;" ::: "memory");
        if (elect_one()) {
            if (warp == 8) {
#pragma unroll 1
                for (int i = STA; i < (extra ? 64 : 32); i++) {
                    const int s = i & 3, k0 = (i & 15) * 64, t = i >> 4;
                    const int c0 = extra ? col0 : col0 + 16 * t;
                    const uint32_t full = full0 + 8 * s, b = base + W_OFF + s * 32768;
                    mbar_wait_p(bars + 8 * (BAR_EMPTY_A + s), ((i >> 2) & 1) ^ 1);
                    TL(2, i, true);
                    mbar_expect_tx(full, 49152);
                    tma_2d(base + s * 16384, &mp.x128, full, k0, (extra ? m_blk + t : m_blk) * 128);
                    tma_3d(b, &mp.w32[0], full, 0, k0, c0);
                    tma_3d(b + 8192, &mp.w32[1], full, 0, k0, c0);
                    tma_3d(b + 16384, &mp.w32[0], full, 0, k0 + 32, c0);
                    tma_3d(b + 24576, &mp.w32[1], full, 0, k0 + 32, c0);
                }
                if (extra) return;
                int xs = 0, ws = 0, w = 0;
#pragma unroll 1
                for (int i = 0; i < 32; i++) {
                    mbar_wait_p(bars + 8 * (BAR_EMPTY_A + (i & 3)), ((i >> 2) & 1) ^ 1);
                    TL(2, 32 + i, true);
                    tma_2d(base + (i & 3) * 16384, &mp.x128, bars + 8 * (BAR_FULL_C + xs), (i & 15) * 64, m_blk * 128);
                    if (++xs == STC) xs = 0;
#pragma unroll 1
                    for (; w <= (i < 2 || i == 31 ? i : i + 1); w++) {
                        const uint32_t full = bars + 8 * (BAR_FULL_C + ws), b = base + W_OFF + ws * 24576;
                        mbar_expect_tx(full, 40960);
                        tma_3d(b, &mp.w64[w >> 4], full, 0, (w & 15) * 64, col0 + 32);
                        tma_3d(b + 16384, &mp.part[w >> 4], full, 0, (w & 15) * 64, (EXP & 1) ? (j_blk & 4) | ((j_blk & 2) ? 3 : 0) : j_blk);
                        if (++ws == STC) ws = 0;
                    }
                }
                const uint8_t* h_src = g_h + (size_t)m_blk * KB_FF * 16384;
                int s = 4, ps = 3;
                uint32_t ph = 1;
#pragma unroll 1
                for (int i = 0; i < KB_FF; i++) {
                    const uint32_t full = bars + 8 * (BAR_FULL_B + s);
                    if (i < STB) mbar_wait_p(bars + 8 * (BAR_EMPTY_A + ((2 * i + 1) / 3)), 1);
                    else mbar_wait_p(bars + 8 * (BAR_EMPTY_B + s), ph);
                    TL(2, 64 + i, true);
                    mbar_expect_tx(full, 32768);
                    tma_3d(base + s * 32768, &mp.d, full, 0, i * 64, col0);
                    if ((i & 15) == 0) mbar_wait_p(bars + 8 * (BAR_HREADY + (i >> 4)), 0);
                    bulk_load(base + ps * 32768 + 16384, h_src + (size_t)i * 16384, 16384, full);
                    ps = s;
                    if (++s == STB) s = 0;
                    if (s == 4) ph ^= 1;
                }
            } else if (warp <= 10) {
                const int w = warp - 9;
#pragma unroll 1
                for (int b = 0; b < (extra ? 8 : 7); b++) {
                    const int t = b >> 1;
                    const bool part = !extra && b == 6;
                    const int m = extra ? m_blk + t : m_blk;
                    const int chunk = part ? 192 + 3 * j_blk : (col0 + (b & 1) + (extra ? 0 : 16 * t)) * 4;
                    uint8_t* dst = g_h + ((size_t)m * (KB_FF * 4) + chunk) * 4096 + w * 2048;
                    const uint32_t src = base + STAGING_OFF + w * 16384 + (b & 1) * 8192;
                    const uint32_t pace = (extra ? t < 3 : t == 0) ? PACE0 : t == 1 ? PACE1 : PACE2;
                    mbar_wait_p(bars + 8 * (BAR_SFULL + 2 * w + (b & 1)), t & 1);
#pragma unroll 1
                    for (int q = 0; q < (part ? 3 : 4); q++) {
                        if (q | (b & 1)) __nanosleep(pace);
                        bulk_store(dst + q * 4096, src + q * 2048, 2048);
                        bulk_commit();
                        asm volatile("cp.async.bulk.wait_group.read 0;" ::: "memory");
                    }
                    mbar_arrive(bars + 8 * (BAR_SEMPTY + 2 * w + (b & 1)));
                    if ((b & 1) || part) {
                        asm volatile("cp.async.bulk.wait_group 0;" ::: "memory");
                        asm volatile("fence.proxy.async.global;" ::: "memory");
                        asm volatile("red.release.gpu.global.add.u32 [%0], %1;"
                                     :: "l"(g_ready + m * 4 + (extra ? 3 : t)), "r"(extra ? 8 : part ? 1 : 2) : "memory");
                    }
                }
            } else {
                TS(0, true);
                uint32_t nsm;
                asm("mov.u32 %0, %%nsmid;" : "=r"(nsm));
                if (smem_u32(smem_raw) != base || nsm != NUM_CTAS) __trap();
                prefetch_map(&mp.w64[0]);
                prefetch_map(&mp.w64[1]);
                prefetch_map(&mp.part[0]);
                prefetch_map(&mp.part[1]);
                prefetch_map(&mp.d);
                prefetch_map(&mp.out);
                if (extra) return;
                const int row = m_blk * 64 + j_blk * 8;
#pragma unroll 1
                for (int i = m_blk & 3; i <= 32 + m_blk; i += 4) {
                    mbar_wait(bars + 8 * (BAR_EMPTY_A + (i & 3)), (i >> 2) & 1);
                    if ((i & 15) != m_blk) continue;
                    const int t = i >> 4;
                    if (t == 2 && (PF & 8)) prefetch_l2(mp.wd + row * 2048, 16384);
                    if (!(PF >> t & 1)) continue;
#pragma unroll 1
                    for (int r = row; r < row + 8; r++) {
                        if (t != 2) prefetch_l2(mp.wg + r * (D_FF * 2) + (t ? 4096 : 2048), t ? 2816 : 2048);
                        if (t != 1) prefetch_l2(mp.wu + r * (D_FF * 2) + (t ? 4096 : 2048), t ? 2816 : 2048);
                    }
                }
#pragma unroll
                for (int round = 0; round < 4; round++) {
                    uint32_t v, it = 0;
                    while (true) {
                        asm volatile("ld.acquire.gpu.global.u32 %0, [%1];" : "=r"(v) : "l"(g_ready + m_blk * 4 + round) : "memory");
                        if (v - (cnt[round] & ~31u) >= 32u) break;
                        if (++it > (1u << 20)) __trap();
                        __nanosleep(POLL);
                    }
                    asm volatile("fence.proxy.async.global;" ::: "memory");
                    mbar_arrive(bars + 8 * (BAR_HREADY + round));
                    TL(2, 122 + round, true);
                }
            }
        }
    }
}

typedef CUresult (*EncodeFn)(CUtensorMap*, CUtensorMapDataType, cuuint32_t, void*, const cuuint64_t*, const cuuint64_t*,
                             const cuuint32_t*, const cuuint32_t*, CUtensorMapInterleave, CUtensorMapSwizzle,
                             CUtensorMapL2promotion, CUtensorMapFloatOOBfill);

void map_2d(EncodeFn enc, CUtensorMap* m, const void* p, int rows, int cols, int box_rows) {
    cuuint64_t dims[2] = {(cuuint64_t)cols, (cuuint64_t)rows};
    cuuint64_t str[1] = {(cuuint64_t)cols * 2};
    cuuint32_t box[2] = {64, (cuuint32_t)box_rows};
    cuuint32_t es[2] = {1, 1};
    enc(m, CU_TENSOR_MAP_DATA_TYPE_BFLOAT16, 2, const_cast<void*>(p), dims, str, box, es, CU_TENSOR_MAP_INTERLEAVE_NONE,
        CU_TENSOR_MAP_SWIZZLE_128B, CU_TENSOR_MAP_L2_PROMOTION_L2_128B, CU_TENSOR_MAP_FLOAT_OOB_FILL_NONE);
}
void map_w(EncodeFn enc, CUtensorMap* m, const void* p, int K, int N, int rows, int atoms) {
    cuuint64_t dims[3] = {64, (cuuint64_t)K, (cuuint64_t)N / 64};
    cuuint64_t str[2] = {(cuuint64_t)N * 2, 128};
    cuuint32_t box[3] = {64, (cuuint32_t)rows, (cuuint32_t)atoms};
    cuuint32_t es[3] = {1, 1, 1};
    enc(m, CU_TENSOR_MAP_DATA_TYPE_BFLOAT16, 3, const_cast<void*>(p), dims, str, box, es, CU_TENSOR_MAP_INTERLEAVE_NONE,
        CU_TENSOR_MAP_SWIZZLE_128B, CU_TENSOR_MAP_L2_PROMOTION_L2_128B, CU_TENSOR_MAP_FLOAT_OOB_FILL_NONE);
}

void map_part(EncodeFn enc, CUtensorMap* m, const void* p) {
    cuuint64_t dims[3] = {48, (cuuint64_t)D_MODEL, 8};
    cuuint64_t str[2] = {(cuuint64_t)D_FF * 2, 96};
    cuuint32_t box[3] = {64, 64, 1};
    cuuint32_t es[3] = {1, 1, 1};
    enc(m, CU_TENSOR_MAP_DATA_TYPE_BFLOAT16, 3, (char*)const_cast<void*>(p) + 3072 * 2, dims, str, box, es, CU_TENSOR_MAP_INTERLEAVE_NONE,
        CU_TENSOR_MAP_SWIZZLE_128B, CU_TENSOR_MAP_L2_PROMOTION_L2_128B, CU_TENSOR_MAP_FLOAT_OOB_FILL_NONE);
}

}

extern "C" void kernel_launch(void* const* d_in, const int* in_sizes, int n_in, void* d_out, int out_size) {
    (void)in_sizes; (void)n_in; (void)out_size;
    void* fn = nullptr;
    cudaDriverEntryPointQueryResult st;
    cudaGetDriverEntryPoint("cuTensorMapEncodeTiled", &fn, cudaEnableDefault, &st);
    EncodeFn enc = (EncodeFn)fn;
    Maps mp;
    map_2d(enc, &mp.x64, d_in[0], M_TOK, D_MODEL, 64);
    map_2d(enc, &mp.x128, d_in[0], M_TOK, D_MODEL, 128);
    map_w(enc, &mp.g16, d_in[1], D_MODEL, D_FF, 16, 2);
    map_w(enc, &mp.u16, d_in[2], D_MODEL, D_FF, 16, 2);
    map_w(enc, &mp.w32[0], d_in[1], D_MODEL, D_FF, 32, 2);
    map_w(enc, &mp.w32[1], d_in[2], D_MODEL, D_FF, 32, 2);
    map_w(enc, &mp.w64[0], d_in[1], D_MODEL, D_FF, 64, 2);
    map_w(enc, &mp.w64[1], d_in[2], D_MODEL, D_FF, 64, 2);
    map_part(enc, &mp.part[0], d_in[1]);
    map_part(enc, &mp.part[1], d_in[2]);
    map_w(enc, &mp.d, d_in[3], D_FF, D_MODEL, 64, 2);
    map_2d(enc, &mp.out, d_out, M_TOK, D_MODEL, 16);
    mp.wg = (const uint8_t*)d_in[1];
    mp.wu = (const uint8_t*)d_in[2];
    mp.wd = (const uint8_t*)d_in[3];
    cudaFuncSetAttribute(geglu_ffn_kernel, cudaFuncAttributeMaxDynamicSharedMemorySize, SMEM_BYTES);
    geglu_ffn_kernel<<<NUM_CTAS, NUM_THREADS, SMEM_BYTES>>>(mp);
}
```

```cpp
#include <cuda_runtime.h>
#include <cuda_bf16.h>
#include <cuda.h>
#include <stdint.h>

namespace {

constexpr int M_TOK = 2048, D_MODEL = 1024, D_FF = 3584;
constexpr int KB_FF = D_FF / 64;
constexpr int NUM_CTAS = 132;
constexpr int NUM_WORK = 128;
constexpr int NUM_THREADS = 384;

constexpr int STA = 4, STC = 5, STB = 6;
constexpr int W_OFF = STA * 16384;
constexpr int RING_BYTES = 196608;
constexpr int STAGING_OFF = RING_BYTES;
constexpr int BAR_OFF = STAGING_OFF + 32768;
#define SMR 1
constexpr int SMEM_BYTES = BAR_OFF + 512 + 1536;
constexpr uint32_t base = 1024, bars = base + BAR_OFF;

constexpr int BAR_FULL_A = 0, BAR_EMPTY_A = 4, BAR_FULL_B = 8, BAR_EMPTY_B = 14, BAR_SFULL = 20, BAR_SEMPTY = 24,
              BAR_HREADY = 28, BAR_FULL_C = 32, BAR_PIECE = 37;

__device__ __align__(1024) uint8_t g_h[(size_t)M_TOK * D_FF * 2];
__device__ __align__(16) unsigned int g_ready[16 * 4];

#define TS(slot, cond)
#define TL(row, idx, cond)
#define TL_DUMP()

__device__ __forceinline__ uint32_t smem_u32(const void* p) { return (uint32_t)__cvta_generic_to_shared(p); }
__device__ __forceinline__ bool elect_one() {
    uint32_t p;
    asm volatile("{\n.reg .pred p;\nelect.sync _|p, 0xffffffff;\nselp.u32 %0, 1, 0, p;\n}" : "=r"(p));
    return p != 0;
}
__device__ __forceinline__ void mbar_init(uint32_t bar, uint32_t cnt) {
    asm volatile("mbarrier.init.shared::cta.b64 [%0], %1;" :: "r"(bar), "r"(cnt) : "memory");
}
__device__ __forceinline__ void mbar_expect_tx(uint32_t bar, uint32_t bytes) {
    asm volatile("mbarrier.arrive.expect_tx.shared::cta.b64 _, [%0], %1;" :: "r"(bar), "r"(bytes) : "memory");
}
__device__ __forceinline__ void mbar_arrive(uint32_t bar) {
    asm volatile("mbarrier.arrive.shared::cta.b64 _, [%0];" :: "r"(bar) : "memory");
}
__device__ __forceinline__ bool mbar_try(uint32_t bar, uint32_t parity) {
    uint32_t done;
    asm volatile("{\n.reg .pred p;\nmbarrier.try_wait.parity.shared::cta.b64 p, [%1], %2;\nselp.u32 %0, 1, 0, p;\n}"
                 : "=r"(done) : "r"(bar), "r"(parity) : "memory");
    return done != 0;
}
__device__ __forceinline__ void mbar_wait_p(uint32_t bar, uint32_t parity) {
    uint32_t it = 0;
#pragma unroll 1
    while (!mbar_try(bar, parity)) {
        if (++it > (1u << 20)) __trap();
    }
}
__device__ __forceinline__ void mbar_wait(uint32_t bar, uint32_t parity) {
    if (mbar_try(bar, parity)) return;
    uint32_t it = 0;
#pragma unroll 1
    while (!mbar_try(bar, parity)) {
        if (++it > (1u << 21)) break;
    }
}
__device__ __forceinline__ void tma_2d(uint32_t dst, const CUtensorMap* m, uint32_t bar, int c0, int c1) {
    asm volatile("cp.async.bulk.tensor.2d.shared::cluster.global.mbarrier::complete_tx::bytes [%0], [%1, {%3, %4}], [%2];"
                 :: "r"(dst), "l"((uint64_t)m), "r"(bar), "r"(c0), "r"(c1) : "memory");
}
__device__ __forceinline__ void tma_3d(uint32_t dst, const CUtensorMap* m, uint32_t bar, int c0, int c1, int c2) {
    asm volatile("cp.async.bulk.tensor.3d.shared::cluster.global.mbarrier::complete_tx::bytes [%0], [%1, {%3, %4, %5}], [%2];"
                 :: "r"(dst), "l"((uint64_t)m), "r"(bar), "r"(c0), "r"(c1), "r"(c2) : "memory");
}
__device__ __forceinline__ void bulk_load(uint32_t dst, const void* src, uint32_t bytes, uint32_t bar) {
    asm volatile("cp.async.bulk.shared::cluster.global.mbarrier::complete_tx::bytes [%0], [%1], %2, [%3];"
                 :: "r"(dst), "l"(src), "r"(bytes), "r"(bar) : "memory");
}
__device__ __forceinline__ void bulk_store(void* dst, uint32_t src, uint32_t bytes) {
    asm volatile("cp.async.bulk.global.shared::cta.bulk_group [%0], [%1], %2;" :: "l"(dst), "r"(src), "r"(bytes) : "memory");
}
__device__ __forceinline__ void tma_store_2d(const CUtensorMap* m, uint32_t src, int c0, int c1) {
    asm volatile("cp.async.bulk.tensor.2d.global.shared::cta.bulk_group [%0, {%2, %3}], [%1];"
                 :: "l"((uint64_t)m), "r"(src), "r"(c0), "r"(c1) : "memory");
}
__device__ __forceinline__ void prefetch_map(const CUtensorMap* m) {
    asm volatile("prefetch.tensormap [%0];" :: "l"((uint64_t)m) : "memory");
}
__device__ __forceinline__ void prefetch_l2(const void* p, uint32_t bytes) {
    asm volatile("cp.async.bulk.prefetch.L2.global [%0], %1;" :: "l"(p), "r"(bytes) : "memory");
}
__device__ __forceinline__ void bulk_commit() { asm volatile("cp.async.bulk.commit_group;" ::: "memory"); }
__device__ __forceinline__ void fence_async_smem() { asm volatile("fence.proxy.async.shared::cta;" ::: "memory"); }
__device__ __forceinline__ void wg_fence() { asm volatile("wgmma.fence.sync.aligned;" ::: "memory"); }
__device__ __forceinline__ void wg_commit() { asm volatile("wgmma.commit_group.sync.aligned;" ::: "memory"); }
template <int N> __device__ __forceinline__ void wg_wait() { asm volatile("wgmma.wait_group.sync.aligned %0;" :: "n"(N) : "memory"); }

constexpr uint32_t HI_SW = (1u << 30) | 64u, HI_H = 16u;
__host__ __device__ constexpr uint32_t desc_lo(uint32_t addr, uint32_t lbo) { return (addr >> 4) | ((lbo >> 4) << 16); }

#define R8(a, o) "+f"(a[o + 0]), "+f"(a[o + 1]), "+f"(a[o + 2]), "+f"(a[o + 3]), "+f"(a[o + 4]), "+f"(a[o + 5]), "+f"(a[o + 6]), "+f"(a[o + 7])
#define R32(a, o) R8(a, o), R8(a, o + 8), R8(a, o + 16), R8(a, o + 24)

template <uint32_t HA, int O = 0, int N>
__device__ __forceinline__ void wgmma_n256(float (&d)[N], uint32_t da, uint32_t db, int scale_d) {
    asm volatile("{\n.reg .pred p;\n.reg .b64 da, db;\nsetp.ne.b32 p, %130, 0;\nmov.b64 da, {%128, %131};\nmov.b64 db, {%129, %132};\n"
        "wgmma.mma_async.sync.aligned.m64n256k16.f32.bf16.bf16 "
        "{%0,%1,%2,%3,%4,%5,%6,%7,%8,%9,%10,%11,%12,%13,%14,%15,%16,%17,%18,%19,%20,%21,%22,%23,%24,%25,%26,%27,%28,%29,%30,%31,"
        "%32,%33,%34,%35,%36,%37,%38,%39,%40,%41,%42,%43,%44,%45,%46,%47,%48,%49,%50,%51,%52,%53,%54,%55,%56,%57,%58,%59,%60,%61,%62,%63,"
        "%64,%65,%66,%67,%68,%69,%70,%71,%72,%73,%74,%75,%76,%77,%78,%79,%80,%81,%82,%83,%84,%85,%86,%87,%88,%89,%90,%91,%92,%93,%94,%95,"
        "%96,%97,%98,%99,%100,%101,%102,%103,%104,%105,%106,%107,%108,%109,%110,%111,%112,%113,%114,%115,%116,%117,%118,%119,%120,%121,%122,%123,%124,%125,%126,%127},"
        " da, db, p, 1, 1, 0, 1;\n}\n"
        : R32(d, O + 0), R32(d, O + 32), R32(d, O + 64), R32(d, O + 96)
        : "r"(da), "r"(db), "r"(scale_d), "n"(HA), "n"(HI_SW));
}
template <uint32_t HA, int O = 0, int N>
__device__ __forceinline__ void wgmma_n176(float (&d)[N], uint32_t da, uint32_t db, int scale_d) {
    asm volatile("{\n.reg .pred p;\n.reg .b64 da, db;\nsetp.ne.b32 p, %90, 0;\nmov.b64 da, {%88, %91};\nmov.b64 db, {%89, %92};\n"
        "wgmma.mma_async.sync.aligned.m64n176k16.f32.bf16.bf16 "
        "{%0,%1,%2,%3,%4,%5,%6,%7,%8,%9,%10,%11,%12,%13,%14,%15,%16,%17,%18,%19,%20,%21,%22,%23,%24,%25,%26,%27,%28,%29,%30,%31,"
        "%32,%33,%34,%35,%36,%37,%38,%39,%40,%41,%42,%43,%44,%45,%46,%47,%48,%49,%50,%51,%52,%53,%54,%55,%56,%57,%58,%59,%60,%61,%62,%63,"
        "%64,%65,%66,%67,%68,%69,%70,%71,%72,%73,%74,%75,%76,%77,%78,%79,%80,%81,%82,%83,%84,%85,%86,%87},"
        " da, db, p, 1, 1, 0, 1;\n}\n"
        : R32(d, O + 0), R32(d, O + 32), R8(d, O + 64), R8(d, O + 72), R8(d, O + 80)
        : "r"(da), "r"(db), "r"(scale_d), "n"(HA), "n"(HI_SW));
}
template <uint32_t HA, int O = 0, int N>
__device__ __forceinline__ void wgmma_n128(float (&d)[N], uint32_t da, uint32_t db, int scale_d) {
    asm volatile("{\n.reg .pred p;\n.reg .b64 da, db;\nsetp.ne.b32 p, %66, 0;\nmov.b64 da, {%64, %67};\nmov.b64 db, {%65, %68};\n"
        "wgmma.mma_async.sync.aligned.m64n128k16.f32.bf16.bf16 "
        "{%0,%1,%2,%3,%4,%5,%6,%7,%8,%9,%10,%11,%12,%13,%14,%15,%16,%17,%18,%19,%20,%21,%22,%23,%24,%25,%26,%27,%28,%29,%30,%31,"
        "%32,%33,%34,%35,%36,%37,%38,%39,%40,%41,%42,%43,%44,%45,%46,%47,%48,%49,%50,%51,%52,%53,%54,%55,%56,%57,%58,%59,%60,%61,%62,%63},"
        " da, db, p, 1, 1, 0, 1;\n}\n"
        : R32(d, O + 0), R32(d, O + 32)
        : "r"(da), "r"(db), "r"(scale_d), "n"(HA), "n"(HI_SW));
}
template <uint32_t HA>
__device__ __forceinline__ void wgmma_n64(float (&d)[32], uint32_t da, uint32_t db, int scale_d) {
    asm volatile("{\n.reg .pred p;\n.reg .b64 da, db;\nsetp.ne.b32 p, %34, 0;\nmov.b64 da, {%32, %35};\nmov.b64 db, {%33, %36};\n"
        "wgmma.mma_async.sync.aligned.m64n64k16.f32.bf16.bf16 "
        "{%0,%1,%2,%3,%4,%5,%6,%7,%8,%9,%10,%11,%12,%13,%14,%15,%16,%17,%18,%19,%20,%21,%22,%23,%24,%25,%26,%27,%28,%29,%30,%31},"
        " da, db, p, 1, 1, 0, 1;\n}\n"
        : R32(d, 0)
        : "r"(da), "r"(db), "r"(scale_d), "n"(HA), "n"(HI_SW));
}
template <int M, int N> __device__ __forceinline__ void fence_regs(float (&d)[N]) {
#pragma unroll
    for (int i = 0; i < M; i++) asm volatile("" : "+f"(d[i]) :: "memory");
}

__device__ __forceinline__ uint32_t pack_bf16(float lo, float hi) {
    uint32_t r;
    asm("cvt.rn.bf16x2.f32 %0, %1, %2;" : "=r"(r) : "f"(hi), "f"(lo));
    return r;
}
__device__ __forceinline__ float gelu_gate(float g) {
    const float K0 = -2.3022081986f;
    const float K1 = -0.1029432397f;
    float t = g * fmaf(g * g, K1, K0);
    float e, r;
    asm("ex2.approx.ftz.f32 %0, %1;" : "=f"(e) : "f"(t));
    asm("rcp.approx.ftz.f32 %0, %1;" : "=f"(r) : "f"(1.0f + e));
    return r;
}
__device__ __forceinline__ float geglu(float g, float u) { return (g * u) * gelu_gate(g); }
__device__ __forceinline__ uint32_t gelu2(float lo, float hi) { return pack_bf16(lo * gelu_gate(lo), hi * gelu_gate(hi)); }
__device__ __forceinline__ uint32_t mul_bf16x2(uint32_t a, uint32_t b) {
    uint32_t r;
    asm("mul.rn.bf16x2 %0, %1, %2;" : "=r"(r) : "r"(a), "r"(b));
    return r;
}
__device__ __forceinline__ uint32_t geglu2(uint32_t g, uint32_t u) {
    float lo = geglu(__uint_as_float(g << 16), __uint_as_float(u << 16));
    float hi = geglu(__uint_as_float(g & 0xffff0000u), __uint_as_float(u & 0xffff0000u));
    return pack_bf16(lo, hi);
}
__device__ __forceinline__ void stsm_x4(uint32_t addr, uint32_t r0, uint32_t r1, uint32_t r2, uint32_t r3) {
    asm volatile("stmatrix.sync.aligned.m8n8.x4.shared.b16 [%0], {%1, %2, %3, %4};"
                 :: "r"(addr), "r"(r0), "r"(r1), "r"(r2), "r"(r3) : "memory");
}

#define PF 15
#define PACE0 300
#define PACE1 800
#define PACE2 0
#define POLL 200
#define TAIL 1
#define TN 5
#define ORD 0
#define PFO 0
#define STG 1
#define EXP 0
struct Maps { CUtensorMap x64, g16, u16, w32[2], x128, w64[2], part[2], d, out; const uint8_t *wg, *wu, *wd; uint8_t* o; };

struct Consumer {
    uint32_t st_h;
    int lane, wg;
    mutable int tl = 0;

    __device__ __forceinline__ void release(int bar_idx) const {
        if (lane == 0) mbar_arrive(bars + 8 * bar_idx);
    }
    __device__ __forceinline__ void wait_full(int bar_idx, uint32_t parity) const { mbar_wait(bars + 8 * bar_idx, parity); }
    __device__ __forceinline__ void stage(int c, uint32_t parity, bool last, uint32_t r0, uint32_t r1, uint32_t r2, uint32_t r3) const {
        if ((c & 3) == 0) mbar_wait(bars + 8 * (BAR_SEMPTY + 2 * wg + ((c >> 2) & 1)), parity);
        stsm_x4(st_h + (c & 7) * 2048, r0, r1, r2, r3);
        if (last) {
            fence_async_smem();
            __syncwarp();
            if (lane == 0) mbar_arrive(bars + 8 * (BAR_SFULL + 2 * wg + ((c >> 2) & 1)));
        }
    }
    __device__ __forceinline__ void stage_geglu(int c, uint32_t parity, const uint32_t (&pk)[64]) const {
        const int q = 4 * c;
        stage(c, parity, (c & 3) == 3, geglu2(pk[q], pk[32 + q]), geglu2(pk[q + 1], pk[33 + q]),
              geglu2(pk[q + 2], pk[34 + q]), geglu2(pk[q + 3], pk[35 + q]));
    }
    __device__ __forceinline__ void mma_a(float (&acc)[128], int s, bool first = false) const {
        TL(wg, tl++, (threadIdx.x & 127) == 0);
        const uint32_t da = desc_lo(base, 16) + s * 1024 + wg * 512, db = desc_lo(base + W_OFF, 4096) + s * 2048;
        wg_fence();
        wgmma_n256<HI_SW>(acc, da, db, first ? 0 : 1);
        wgmma_n256<HI_SW>(acc, da + 2, db + 128, 1);
        wgmma_n256<HI_SW>(acc, da + 4, db + 1024, 1);
        wgmma_n256<HI_SW>(acc, da + 6, db + 1152, 1);
        wg_commit();
    }
    template <int N>
    __device__ __forceinline__ void mma_c(float (&acc)[N], int s, int ws, bool first = false) const {
        TL(wg, tl++, (threadIdx.x & 127) == 0);
        const uint32_t da = desc_lo(base, 16) + s * 1024 + wg * 512, db = desc_lo(base + W_OFF, 8192) + ws * 1536;
        wg_fence();
        wgmma_n176<HI_SW>(acc, da, db, first ? 0 : 1);
        wgmma_n176<HI_SW>(acc, da + 2, db + 128, 1);
        wgmma_n176<HI_SW>(acc, da + 4, db + 256, 1);
        wgmma_n176<HI_SW>(acc, da + 6, db + 384, 1);
        wg_commit();
    }
    __device__ __forceinline__ void mma_b(float (&acc)[64], int s, int ps, bool first = false) const {
        TL(wg, tl++, (threadIdx.x & 127) == 0);
        const uint32_t da = desc_lo(base + 16384, 128) + ps * 2048 + wg * 128, db = desc_lo(base, 8192) + s * 2048;
        wg_fence();
        wgmma_n128<HI_H>(acc, da, db, first ? 0 : 1);
        wgmma_n128<HI_H>(acc, da + 256, db + 128, 1);
        wgmma_n128<HI_H>(acc, da + 512, db + 256, 1);
        wgmma_n128<HI_H>(acc, da + 768, db + 384, 1);
        wg_commit();
    }
    __device__ __forceinline__ void step_a(float (&acc)[128], int kb) const {
        mma_a(acc, kb & 3);
        release(BAR_EMPTY_A + ((kb - 1) & 3));
    }
    __device__ __forceinline__ void next_a(int kb) const { wait_full(BAR_FULL_A + ((kb + 1) & 3), ((kb + 1) >> 2) & 1); }
    template <int N>
    __device__ __forceinline__ void step_c(float (&acc)[N], int kb, int ws, bool first = false) const {
        mma_c(acc, kb & 3, ws, first);
        release(BAR_EMPTY_A + ((kb - 1) & 3));
    }
    __device__ __forceinline__ void next_c(int kb) const { wait_full(BAR_FULL_C + (kb + 1) % STC, ((kb + 1) / STC) & 1); }
};

__global__ void __launch_bounds__(NUM_THREADS, 1) geglu_ffn_kernel(const __grid_constant__ Maps mp) {
    extern __shared__ __align__(1024) uint8_t smem_raw[];
    const int warp = __shfl_sync(0xffffffffu, threadIdx.x >> 5, 0);
    const int lane = threadIdx.x & 31;

    uint32_t sm;
    asm("mov.u32 %0, %%smid;" : "=r"(sm));
    const int tpc = sm >> 1;
    const int q7 = ((tpc - 32) * 37) >> 8;
    const bool extra = (tpc >> 1) == 30;
    const int grp = tpc < 32 ? tpc & 7 : tpc < 60 ? tpc - 31 - 7 * q7 : 0;
    const int j_blk = tpc < 32 ? tpc >> 3 : tpc < 60 ? 4 + q7 : tpc - 58;
    const int m_blk = extra ? (sm & 3) * 4 : grp * 2 + (sm & 1);
    const int col0 = extra ? 54 : j_blk * 2;

    const uint32_t full0 = bars + 8 * BAR_FULL_A, piece = bars + 8 * BAR_PIECE;
    if (warp == 8) {
        if (elect_one()) {
            mbar_init(full0, 1);
            mbar_init(piece, 1);
            mbar_init(piece + 8, 1);
            mbar_init(piece + 16, 1);
            asm volatile("fence.mbarrier_init.release.cluster;" ::: "memory");
            TL(2, 0, true);
            mbar_expect_tx(full0, 16384);
            tma_2d(base, &mp.x64, full0, 0, m_blk * 128);
            tma_3d(base + W_OFF, &mp.g16, full0, 0, 0, col0);
            tma_3d(base + W_OFF + 4096, &mp.u16, full0, 0, 0, col0);
            mbar_expect_tx(piece, 8192);
            tma_2d(base + 8192, &mp.x64, piece, 0, m_blk * 128 + 64);
            mbar_expect_tx(piece + 8, 8192);
            tma_3d(base + W_OFF + 8192, &mp.g16, piece + 8, 0, 16, col0);
            tma_3d(base + W_OFF + 12288, &mp.u16, piece + 8, 0, 16, col0);
            mbar_expect_tx(piece + 16, 16384);
            tma_3d(base + W_OFF + 16384, &mp.w32[0], piece + 16, 0, 32, col0);
            tma_3d(base + W_OFF + 24576, &mp.w32[1], piece + 16, 0, 32, col0);
            TL(2, 121, true);
            mbar_init(full0 + 8, 1);
            mbar_init(full0 + 16, 1);
            mbar_init(full0 + 24, 1);
            mbar_init(piece + 24, 1);
            asm volatile("fence.mbarrier_init.release.cluster;" ::: "memory");
        }
        __syncwarp();
        asm volatile("bar.arrive 4, 384;" ::: "memory");
    } else {
        asm volatile("bar.sync 4, 384;" ::: "memory");
        asm volatile("nanosleep.u32 0;" ::: "memory");
    }

    if (warp < 8) {
        TL(0, 121, threadIdx.x == 0);
        if (warp == 0) {
            if (elect_one()) {
#pragma unroll
                for (int i = BAR_EMPTY_A; i < BAR_PIECE; i++) {
                    const bool empty = (i >= BAR_EMPTY_A && i < BAR_FULL_B) || (i >= BAR_EMPTY_B && i < BAR_SFULL);
                    mbar_init(bars + 8 * i, empty ? 8 : (i >= BAR_SFULL && i < BAR_SEMPTY) ? 4 : 1);
                }
                asm volatile("fence.mbarrier_init.release.cluster;" ::: "memory");
            }
            __syncwarp();
            asm volatile("bar.arrive 2, 160;" ::: "memory");
        }
        asm volatile("setmaxnreg.inc.sync.aligned.u32 240;");
        TL(0, 123, threadIdx.x == 0);
        asm volatile("bar.sync 1, 256;" ::: "memory");
        TL(0, 122, threadIdx.x == 0);
        Consumer c;
        c.lane = lane;
        c.wg = warp >> 2;
        c.st_h = base + STAGING_OFF + c.wg * 16384 + (warp & 3) * 512 + (lane & 8) * 32 + (lane >> 4) * 128 + (lane & 7) * 16;
        const bool always = sm != 0xffffffffu;

        float acc[128];
        uint32_t pk[64];
#pragma unroll
        for (int i = 0; i < 64; i++) asm volatile("" : "=r"(pk[i]));
#pragma unroll
        for (int i = 0; i < 128; i++) asm volatile("" : "=f"(acc[i]));

        {
            const uint32_t da = desc_lo(base, 16) + c.wg * 512, da1 = da + 1024;
            constexpr uint32_t dq = desc_lo(base + W_OFF, 2048), dh = desc_lo(base + W_OFF, 4096), dh1 = dh + 2048;
            c.wait_full(c.wg ? BAR_PIECE : BAR_FULL_A, 0);
            c.wait_full(BAR_FULL_A, 0);
            TL(0, 124, threadIdx.x == 0);
            TL(c.wg, c.tl++, (threadIdx.x & 127) == 0);
            wg_fence();
            wgmma_n256<HI_SW>(acc, da, dq, 0);
            TS(1, threadIdx.x == 0);
            c.wait_full(BAR_PIECE + 1, 0);
            wg_fence();
            wgmma_n256<HI_SW>(acc, da + 2, dq + 512, 1);
            c.wait_full(BAR_PIECE + 2, 0);
            wg_fence();
            wgmma_n256<HI_SW>(acc, da + 4, dh + 1024, 1);
            wgmma_n256<HI_SW>(acc, da + 6, dh + 1152, 1);
            wg_commit();
            c.wait_full(BAR_FULL_A + 1, 0);
            TL(c.wg, c.tl++, (threadIdx.x & 127) == 0);
            wg_fence();
            wgmma_n256<HI_SW>(acc, da1, dh1, 1);
            wgmma_n256<HI_SW>(acc, da1 + 2, dh1 + 128, 1);
            c.wait_full(BAR_PIECE + 3, 0);
            if (ORD && c.wg) asm volatile("bar.sync 6, 256;" ::: "memory");
            wg_fence();
            wgmma_n256<HI_SW>(acc, da1 + 4, dh1 + 1024, 1);
            wgmma_n256<HI_SW>(acc, da1 + 6, dh1 + 1152, 1);
            wg_commit();
            if (ORD && !c.wg) asm volatile("bar.arrive 6, 256;" ::: "memory");
            wg_wait<1>();
            c.release(BAR_EMPTY_A);
            c.wait_full(BAR_FULL_A + 2, 0);
        }

        const int last = extra ? 3 : 1;
#pragma unroll 1
        for (int t = 0;; t++) {
#pragma unroll
            for (int kb = 2; kb < 10; kb++) {
                wg_wait<0>();
                c.step_a(acc, kb);
                if (t > 0) c.stage_geglu(kb - 2, t & 1, pk);
                c.next_a(kb);
            }
#pragma unroll 1
            for (int kb = 10; kb < 15; kb++) {
                wg_wait<0>();
                c.step_a(acc, kb);
                c.next_a(kb);
            }
            c.mma_a(acc, 3);
            wg_wait<1>();
            c.release(BAR_EMPTY_A + 2);
            if (t < 3) c.wait_full(t == last ? BAR_FULL_C : BAR_FULL_A, 0);
            wg_wait<0>();
            fence_regs<128>(acc);
            c.release(BAR_EMPTY_A + 3);
#pragma unroll
            for (int i = 0; i < 64; i++) pk[i] = pack_bf16(acc[2 * i], acc[2 * i + 1]);
            TS(2 + t, threadIdx.x == 0);
            if (t == last) break;
            c.mma_a(acc, 0, true);
            c.wait_full(BAR_FULL_A + 1, 0);
            c.mma_a(acc, 1);
            wg_wait<1>();
            c.release(BAR_EMPTY_A);
            c.wait_full(BAR_FULL_A + 2, 0);
        }
        if (extra) {
#pragma unroll
            for (int q = 0; q < 8; q++) c.stage_geglu(q, 0, pk);
            TS(7, threadIdx.x == 0);
            TL(c.wg, 126, (threadIdx.x & 127) == 0);
            TL_DUMP();
            return;
        }

        c.mma_c(acc, 0, 0, true);
        c.next_c(0);
        c.mma_c(acc, 1, 1);
        wg_wait<1>();
        c.release(BAR_EMPTY_A);
        c.next_c(1);
#pragma unroll
        for (int kb = 2; kb < 10; kb++) {
            wg_wait<0>();
            c.step_c(acc, kb, kb % STC);
            if (always) c.stage_geglu(kb - 2, 0, pk);
            c.next_c(kb);
        }
#pragma unroll 1
        for (int kb = 10; kb < 16; kb++) {
            wg_wait<0>();
            c.step_c(acc, kb, kb < 15 ? kb - 10 : 0);
            c.wait_full(BAR_FULL_C + (kb < 14 ? kb - 9 : kb - 14), kb >= 14);
        }
        TS(4, threadIdx.x == 0);

        float acc3[88];
        uint32_t gp[44];
#pragma unroll
        for (int kb = 0; kb < 11; kb++) {
            wg_wait<0>();
            if (kb == 0) fence_regs<88>(acc);
            c.step_c(acc3, kb, (16 + kb) % STC, kb == 0);
#pragma unroll
            for (int i = 40 - 4 * kb; i < 44 - 4 * kb; i++) asm volatile("" : "=r"(gp[i]));
            if (always) {
#pragma unroll
                for (int i = 40 - 4 * kb; i < 44 - 4 * kb; i++) {
                    gp[i] = gelu2(acc[2 * i], acc[2 * i + 1]);
                    asm volatile("" : "+r"(gp[i]));
                }
            }
            c.next_c(16 + kb);
        }
#pragma unroll 1
        for (int kb = 11; kb < 16; kb++) {
            wg_wait<0>();
            c.step_c(acc3, kb, kb < 14 ? kb - 9 : kb - 14);
            c.wait_full(kb < 13 ? BAR_FULL_C + kb - 8 : kb < 15 ? BAR_FULL_C + kb - 13 : BAR_FULL_B + 4, kb < 13);
        }
        TS(5, threadIdx.x == 0);

        float acc4[64];
#pragma unroll
        for (int kb = 0; kb < 11; kb++) {
            wg_wait<0>();
            if (kb == 0) fence_regs<88>(acc3);
            c.mma_b(acc4, (kb + 4) % STB, (kb + 3) % STB, kb == 0);
            c.release(kb == 0 ? BAR_EMPTY_A + 3 : BAR_EMPTY_B + (kb + 3) % STB);
            if (always) {
                const int q = 4 * kb, r = 8 * kb;
                c.stage(kb, kb < 8, (kb & 3) == 3 || kb == 10,
                        mul_bf16x2(gp[q], pack_bf16(acc3[r], acc3[r + 1])), mul_bf16x2(gp[q + 1], pack_bf16(acc3[r + 2], acc3[r + 3])),
                        mul_bf16x2(gp[q + 2], pack_bf16(acc3[r + 4], acc3[r + 5])), mul_bf16x2(gp[q + 3], pack_bf16(acc3[r + 6], acc3[r + 7])));
            }
            c.wait_full(BAR_FULL_B + (kb + 5) % STB, ((kb + 1) / STB) & 1);
        }
        int s = 15 % STB, ps = 14 % STB;
        uint32_t ph = (11 / STB) & 1;
#pragma unroll 1
        for (int kb = 11; kb < KB_FF - (TAIL ? TN : 0); kb++) {
            wg_wait<0>();
            c.mma_b(acc4, s, ps);
            c.release(BAR_EMPTY_B + ps);
            ps = s;
            if (++s == STB) s = 0;
            if (s == 4) ph ^= 1;
            if (TAIL || kb < KB_FF - 1) c.wait_full(BAR_FULL_B + s, ph);
        }
        c.wait_full(BAR_SEMPTY + 2 * c.wg, 1);
        c.wait_full(BAR_SEMPTY + 2 * c.wg + 1, 0);
        const uint32_t strip = base + STAGING_OFF + c.wg * 16384 + (warp & 3) * 2048;
        const uint32_t st_row = strip + (lane & 15) * 128, st_sw = ((lane >> 4) ^ (lane & 7)) << 4;
        const int row0 = m_blk * 128 + warp * 16;
        const uint32_t ld_row = strip + (lane >> 3) * 128 + (((lane & 7) ^ (lane >> 3)) << 4);
        uint8_t* optr = mp.o + (size_t)(row0 + (lane >> 3)) * 2048 + j_blk * 256 + (lane & 7) * 16;
        if (c.wg) asm volatile("bar.sync 6, 256;" ::: "memory");
#pragma unroll
        for (int kb = KB_FF - TN; kb < KB_FF; kb++) {
            if (kb > KB_FF - TN) c.wait_full(BAR_FULL_B + (kb + 4) % STB, (kb / STB) & 1);
            c.mma_b(acc4, (kb + 4) % STB, (kb + 3) % STB);
        }
        if (!c.wg) asm volatile("bar.arrive 6, 256;" ::: "memory");

#pragma unroll
        for (int h = 0; h < 2; h++) {
            if (h == 0) {
                wg_wait<0>();
                fence_regs<64>(acc4);
                TS(6, threadIdx.x == 0);
                TL(c.wg, 125, (threadIdx.x & 127) == 0);
            }
#pragma unroll
            for (int q = 0; q < 4; q++) {
                const int i = 32 * h + 8 * q;
                stsm_x4(st_row + h * 8192 + (st_sw ^ (q << 5)), pack_bf16(acc4[i], acc4[i + 1]), pack_bf16(acc4[i + 2], acc4[i + 3]),
                        pack_bf16(acc4[i + 4], acc4[i + 5]), pack_bf16(acc4[i + 6], acc4[i + 7]));
            }
            if (STG == 2 || (STG == 1 && c.wg) || (STG == 3 && c.wg && h == 1) || (STG == 4 && c.wg && h == 0)) {
                __syncwarp();
                uint4 v[4];
#pragma unroll
                for (int i = 0; i < 4; i++)
                    asm volatile("ld.shared.v4.u32 {%0, %1, %2, %3}, [%4];" : "=r"(v[i].x), "=r"(v[i].y), "=r"(v[i].z), "=r"(v[i].w)
                                 : "r"((ld_row ^ ((i & 1) << 6)) + i * 512 + h * 8192) : "memory");
#pragma unroll
                for (int i = 0; i < 4; i++)
                    asm volatile("st.global.v4.u32 [%0], {%1, %2, %3, %4};" :: "l"(optr + i * 8192 + h * 128), "r"(v[i].x), "r"(v[i].y), "r"(v[i].z), "r"(v[i].w) : "memory");
            } else {
                fence_async_smem();
                __syncwarp();
                if (elect_one()) {
                    tma_store_2d(&mp.out, strip + h * 8192, j_blk * 128 + h * 64, row0);
                    bulk_commit();
                }
            }
        }
        if (elect_one()) asm volatile("cp.async.bulk.wait_group.read 0;" ::: "memory");
        __syncwarp();
        TL(c.wg, 126, (threadIdx.x & 127) == 0);
        TS(7, threadIdx.x == 0);
        TL_DUMP();
    } else {
        asm volatile("setmaxnreg.dec.sync.aligned.u32 24;");
        if (warp == 8 && elect_one()) {
#pragma unroll 1
            for (int i = 1; i < STA; i++) {
                const uint32_t f = full0 + 8 * i, f2 = i == 1 ? piece + 24 : f, b = base + W_OFF + i * 32768;
                TL(2, i, true);
                mbar_expect_tx(f, i == 1 ? 32768 : 49152);
                if (i == 1) mbar_expect_tx(f2, 16384);
                tma_2d(base + i * 16384, &mp.x128, f, i * 64, m_blk * 128);
                tma_3d(b, &mp.w32[0], f, 0, i * 64, col0);
                tma_3d(b + 8192, &mp.w32[1], f, 0, i * 64, col0);
                tma_3d(b + 16384, &mp.w32[0], f2, 0, i * 64 + 32, col0);
                tma_3d(b + 24576, &mp.w32[1], f2, 0, i * 64 + 32, col0);
            }
        }
        __syncwarp();
        asm volatile("bar.sync 2, 160;" ::: "memory");
        uint32_t cnt[4];
        if (warp == 11)
            asm volatile("ld.relaxed.gpu.global.v4.u32 {%0, %1, %2, %3}, [%4];"
                         : "=r"(cnt[0]), "=r"(cnt[1]), "=r"(cnt[2]), "=r"(cnt[3]) : "l"(g_ready + m_blk * 4) : "memory");
        if (warp > 8) asm volatile("bar.sync 5, 96;" ::: "memory");
        if (elect_one()) {
            if (warp == 8) {
#pragma unroll 1
                for (int i = STA; i < (extra ? 64 : 32); i++) {
                    const int s = i & 3, k0 = (i & 15) * 64, t = i >> 4;
                    const int c0 = extra ? col0 : col0 + 16 * t;
                    const uint32_t full = full0 + 8 * s, b = base + W_OFF + s * 32768;
                    mbar_wait_p(bars + 8 * (BAR_EMPTY_A + s), ((i >> 2) & 1) ^ 1);
                    TL(2, i, true);
                    mbar_expect_tx(full, 49152);
                    tma_2d(base + s * 16384, &mp.x128, full, k0, (extra ? m_blk + t : m_blk) * 128);
                    tma_3d(b, &mp.w32[0], full, 0, k0, c0);
                    tma_3d(b + 8192, &mp.w32[1], full, 0, k0, c0);
                    tma_3d(b + 16384, &mp.w32[0], full, 0, k0 + 32, c0);
                    tma_3d(b + 24576, &mp.w32[1], full, 0, k0 + 32, c0);
                }
                if (extra) return;
                int xs = 0, ws = 0, w = 0;
#pragma unroll 1
                for (int i = 0; i < 32; i++) {
                    mbar_wait_p(bars + 8 * (BAR_EMPTY_A + (i & 3)), ((i >> 2) & 1) ^ 1);
                    TL(2, 32 + i, true);
                    tma_2d(base + (i & 3) * 16384, &mp.x128, bars + 8 * (BAR_FULL_C + xs), (i & 15) * 64, m_blk * 128);
                    if (++xs == STC) xs = 0;
#pragma unroll 1
                    for (; w <= (i < 2 || i == 31 ? i : i + 1); w++) {
                        const uint32_t full = bars + 8 * (BAR_FULL_C + ws), b = base + W_OFF + ws * 24576;
                        mbar_expect_tx(full, 40960);
                        tma_3d(b, &mp.w64[w >> 4], full, 0, (w & 15) * 64, col0 + 32);
                        tma_3d(b + 16384, &mp.part[w >> 4], full, 0, (w & 15) * 64, (EXP & 1) ? (j_blk & 4) | ((j_blk & 2) ? 3 : 0) : j_blk);
                        if (++ws == STC) ws = 0;
                    }
                }
                const uint8_t* h_src = g_h + (size_t)m_blk * KB_FF * 16384;
                int s = 4, ps = 3;
                uint32_t ph = 1;
#pragma unroll 1
                for (int i = 0; i < KB_FF; i++) {
                    const uint32_t full = bars + 8 * (BAR_FULL_B + s);
                    if (i < STB) mbar_wait_p(bars + 8 * (BAR_EMPTY_A + ((2 * i + 1) / 3)), 1);
                    else mbar_wait_p(bars + 8 * (BAR_EMPTY_B + s), ph);
                    TL(2, 64 + i, true);
                    mbar_expect_tx(full, 32768);
                    tma_3d(base + s * 32768, &mp.d, full, 0, i * 64, col0);
                    if ((i & 15) == 0) mbar_wait_p(bars + 8 * (BAR_HREADY + (i >> 4)), 0);
                    if (PFO && i == 54) prefetch_map(&mp.out);
                    bulk_load(base + ps * 32768 + 16384, h_src + (size_t)i * 16384, 16384, full);
                    ps = s;
                    if (++s == STB) s = 0;
                    if (s == 4) ph ^= 1;
                }
            } else if (warp <= 10) {
                const int w = warp - 9;
#pragma unroll 1
                for (int b = 0; b < (extra ? 8 : 7); b++) {
                    const int t = b >> 1;
                    const bool part = !extra && b == 6;
                    const int m = extra ? m_blk + t : m_blk;
                    const int chunk = part ? 192 + 3 * j_blk : (col0 + (b & 1) + (extra ? 0 : 16 * t)) * 4;
                    uint8_t* dst = g_h + ((size_t)m * (KB_FF * 4) + chunk) * 4096 + w * 2048;
                    const uint32_t src = base + STAGING_OFF + w * 16384 + (b & 1) * 8192;
                    const uint32_t pace = (extra ? t < 3 : t == 0) ? PACE0 : t == 1 ? PACE1 : PACE2;
                    mbar_wait_p(bars + 8 * (BAR_SFULL + 2 * w + (b & 1)), t & 1);
#pragma unroll 1
                    for (int q = 0; q < (part ? 3 : 4); q++) {
                        if (q | (b & 1)) __nanosleep(pace);
                        bulk_store(dst + q * 4096, src + q * 2048, 2048);
                        bulk_commit();
                        asm volatile("cp.async.bulk.wait_group.read 0;" ::: "memory");
                    }
                    mbar_arrive(bars + 8 * (BAR_SEMPTY + 2 * w + (b & 1)));
                    if ((b & 1) || part) {
                        asm volatile("cp.async.bulk.wait_group 0;" ::: "memory");
                        asm volatile("fence.proxy.async.global;" ::: "memory");
                        asm volatile("red.release.gpu.global.add.u32 [%0], %1;"
                                     :: "l"(g_ready + m * 4 + (extra ? 3 : t)), "r"(extra ? 8 : part ? 1 : 2) : "memory");
                    }
                }
            } else {
                TS(0, true);
                uint32_t nsm;
                asm("mov.u32 %0, %%nsmid;" : "=r"(nsm));
                if (smem_u32(smem_raw) != base || nsm != NUM_CTAS) __trap();
                prefetch_map(&mp.w64[0]);
                prefetch_map(&mp.w64[1]);
                prefetch_map(&mp.part[0]);
                prefetch_map(&mp.part[1]);
                prefetch_map(&mp.d);
                prefetch_map(&mp.out);
                if (extra) return;
                const int row = m_blk * 64 + j_blk * 8;
#pragma unroll 1
                for (int i = m_blk & 3; i <= 32 + m_blk; i += 4) {
                    mbar_wait(bars + 8 * (BAR_EMPTY_A + (i & 3)), (i >> 2) & 1);
                    if ((i & 15) != m_blk) continue;
                    const int t = i >> 4;
                    if (t == 2 && (PF & 8)) prefetch_l2(mp.wd + row * 2048, 16384);
                    if (!(PF >> t & 1)) continue;
#pragma unroll 1
                    for (int r = row; r < row + 8; r++) {
                        if (t != 2) prefetch_l2(mp.wg + r * (D_FF * 2) + (t ? 4096 : 2048), t ? 2816 : 2048);
                        if (t != 1) prefetch_l2(mp.wu + r * (D_FF * 2) + (t ? 4096 : 2048), t ? 2816 : 2048);
                    }
                }
#pragma unroll
                for (int round = 0; round < 4; round++) {
                    uint32_t v, it = 0;
                    while (true) {
                        asm volatile("ld.acquire.gpu.global.u32 %0, [%1];" : "=r"(v) : "l"(g_ready + m_blk * 4 + round) : "memory");
                        if (v - (cnt[round] & ~31u) >= 32u) break;
                        if (++it > (1u << 20)) __trap();
                        __nanosleep(POLL);
                    }
                    asm volatile("fence.proxy.async.global;" ::: "memory");
                    mbar_arrive(bars + 8 * (BAR_HREADY + round));
                    TL(2, 122 + round, true);
                }
            }
        }
    }
}

typedef CUresult (*EncodeFn)(CUtensorMap*, CUtensorMapDataType, cuuint32_t, void*, const cuuint64_t*, const cuuint64_t*,
                             const cuuint32_t*, const cuuint32_t*, CUtensorMapInterleave, CUtensorMapSwizzle,
                             CUtensorMapL2promotion, CUtensorMapFloatOOBfill);

void map_2d(EncodeFn enc, CUtensorMap* m, const void* p, int rows, int cols, int box_rows) {
    cuuint64_t dims[2] = {(cuuint64_t)cols, (cuuint64_t)rows};
    cuuint64_t str[1] = {(cuuint64_t)cols * 2};
    cuuint32_t box[2] = {64, (cuuint32_t)box_rows};
    cuuint32_t es[2] = {1, 1};
    enc(m, CU_TENSOR_MAP_DATA_TYPE_BFLOAT16, 2, const_cast<void*>(p), dims, str, box, es, CU_TENSOR_MAP_INTERLEAVE_NONE,
        CU_TENSOR_MAP_SWIZZLE_128B, CU_TENSOR_MAP_L2_PROMOTION_L2_128B, CU_TENSOR_MAP_FLOAT_OOB_FILL_NONE);
}
void map_w(EncodeFn enc, CUtensorMap* m, const void* p, int K, int N, int rows, int atoms) {
    cuuint64_t dims[3] = {64, (cuuint64_t)K, (cuuint64_t)N / 64};
    cuuint64_t str[2] = {(cuuint64_t)N * 2, 128};
    cuuint32_t box[3] = {64, (cuuint32_t)rows, (cuuint32_t)atoms};
    cuuint32_t es[3] = {1, 1, 1};
    enc(m, CU_TENSOR_MAP_DATA_TYPE_BFLOAT16, 3, const_cast<void*>(p), dims, str, box, es, CU_TENSOR_MAP_INTERLEAVE_NONE,
        CU_TENSOR_MAP_SWIZZLE_128B, CU_TENSOR_MAP_L2_PROMOTION_L2_128B, CU_TENSOR_MAP_FLOAT_OOB_FILL_NONE);
}

void map_part(EncodeFn enc, CUtensorMap* m, const void* p) {
    cuuint64_t dims[3] = {48, (cuuint64_t)D_MODEL, 8};
    cuuint64_t str[2] = {(cuuint64_t)D_FF * 2, 96};
    cuuint32_t box[3] = {64, 64, 1};
    cuuint32_t es[3] = {1, 1, 1};
    enc(m, CU_TENSOR_MAP_DATA_TYPE_BFLOAT16, 3, (char*)const_cast<void*>(p) + 3072 * 2, dims, str, box, es, CU_TENSOR_MAP_INTERLEAVE_NONE,
        CU_TENSOR_MAP_SWIZZLE_128B, CU_TENSOR_MAP_L2_PROMOTION_L2_128B, CU_TENSOR_MAP_FLOAT_OOB_FILL_NONE);
}

}

extern "C" void kernel_launch(void* const* d_in, const int* in_sizes, int n_in, void* d_out, int out_size) {
    (void)in_sizes; (void)n_in; (void)out_size;
    void* fn = nullptr;
    cudaDriverEntryPointQueryResult st;
    cudaGetDriverEntryPoint("cuTensorMapEncodeTiled", &fn, cudaEnableDefault, &st);
    EncodeFn enc = (EncodeFn)fn;
    Maps mp;
    map_2d(enc, &mp.x64, d_in[0], M_TOK, D_MODEL, 64);
    map_2d(enc, &mp.x128, d_in[0], M_TOK, D_MODEL, 128);
    map_w(enc, &mp.g16, d_in[1], D_MODEL, D_FF, 16, 2);
    map_w(enc, &mp.u16, d_in[2], D_MODEL, D_FF, 16, 2);
    map_w(enc, &mp.w32[0], d_in[1], D_MODEL, D_FF, 32, 2);
    map_w(enc, &mp.w32[1], d_in[2], D_MODEL, D_FF, 32, 2);
    map_w(enc, &mp.w64[0], d_in[1], D_MODEL, D_FF, 64, 2);
    map_w(enc, &mp.w64[1], d_in[2], D_MODEL, D_FF, 64, 2);
    map_part(enc, &mp.part[0], d_in[1]);
    map_part(enc, &mp.part[1], d_in[2]);
    map_w(enc, &mp.d, d_in[3], D_FF, D_MODEL, 64, 2);
    map_2d(enc, &mp.out, d_out, M_TOK, D_MODEL, 16);
    mp.wg = (const uint8_t*)d_in[1];
    mp.wu = (const uint8_t*)d_in[2];
    mp.wd = (const uint8_t*)d_in[3];
    mp.o = (uint8_t*)d_out;
    cudaFuncSetAttribute(geglu_ffn_kernel, cudaFuncAttributeMaxDynamicSharedMemorySize, SMEM_BYTES);
    geglu_ffn_kernel<<<NUM_CTAS, NUM_THREADS, SMEM_BYTES>>>(mp);
}
```

```cpp
#include <cuda_runtime.h>
#include <cuda_bf16.h>
#include <cuda.h>
#include <stdint.h>

namespace {

constexpr int M_TOK = 2048, D_MODEL = 1024, D_FF = 3584;
constexpr int KB_FF = D_FF / 64;
constexpr int NUM_CTAS = 132;
constexpr int NUM_WORK = 128;
constexpr int NUM_THREADS = 384;

constexpr int STA = 4, STB = 6;
constexpr int RING_BYTES = 196608;
constexpr int STAGING_OFF = RING_BYTES;
constexpr int BAR_OFF = STAGING_OFF + 32768;
constexpr int SMEM_BYTES = BAR_OFF + 512 + 1536;
constexpr uint32_t base = 1024, bars = base + BAR_OFF;

constexpr int BAR_FULL_A = 0, BAR_EMPTY_A = 4, BAR_FULL_B = 8, BAR_EMPTY_B = 14, BAR_SFULL = 20, BAR_SEMPTY = 24,
              BAR_HREADY = 28, BAR_PF = 32, BAR_FULL_C = 35, BAR_EMPTY_C = 41, BAR_PIECE = 47;

__device__ __align__(1024) uint8_t g_h[(size_t)M_TOK * D_FF * 2];
__device__ __align__(16) unsigned int g_ready[16 * 4];

#define TS(slot, cond)
#define TL(row, idx, cond)
#define TL_DUMP()

__device__ __forceinline__ uint32_t smem_u32(const void* p) { return (uint32_t)__cvta_generic_to_shared(p); }
__device__ __forceinline__ bool elect_one() {
    uint32_t p;
    asm volatile("{\n.reg .pred p;\nelect.sync _|p, 0xffffffff;\nselp.u32 %0, 1, 0, p;\n}" : "=r"(p));
    return p != 0;
}
__device__ __forceinline__ void mbar_init(uint32_t bar, uint32_t cnt) {
    asm volatile("mbarrier.init.shared::cta.b64 [%0], %1;" :: "r"(bar), "r"(cnt) : "memory");
}
__device__ __forceinline__ void mbar_expect_tx(uint32_t bar, uint32_t bytes) {
    asm volatile("mbarrier.arrive.expect_tx.shared::cta.b64 _, [%0], %1;" :: "r"(bar), "r"(bytes) : "memory");
}
__device__ __forceinline__ void mbar_arrive(uint32_t bar) {
    asm volatile("mbarrier.arrive.shared::cta.b64 _, [%0];" :: "r"(bar) : "memory");
}
__device__ __forceinline__ bool mbar_try(uint32_t bar, uint32_t parity) {
    uint32_t done;
    asm volatile("{\n.reg .pred p;\nmbarrier.try_wait.parity.shared::cta.b64 p, [%1], %2;\nselp.u32 %0, 1, 0, p;\n}"
                 : "=r"(done) : "r"(bar), "r"(parity) : "memory");
    return done != 0;
}
__device__ __forceinline__ void mbar_wait_p(uint32_t bar, uint32_t parity) {
    uint32_t it = 0;
#pragma unroll 1
    while (!mbar_try(bar, parity)) {
        if (++it > (1u << 20)) __trap();
    }
}
__device__ __forceinline__ void mbar_wait(uint32_t bar, uint32_t parity) {
    if (mbar_try(bar, parity)) return;
    uint32_t it = 0;
#pragma unroll 1
    while (!mbar_try(bar, parity)) {
        if (++it > (1u << 21)) break;
    }
}
__device__ __forceinline__ void tma_2d(uint32_t dst, const CUtensorMap* m, uint32_t bar, int c0, int c1) {
    asm volatile("cp.async.bulk.tensor.2d.shared::cluster.global.mbarrier::complete_tx::bytes [%0], [%1, {%3, %4}], [%2];"
                 :: "r"(dst), "l"((uint64_t)m), "r"(bar), "r"(c0), "r"(c1) : "memory");
}
__device__ __forceinline__ void tma_3d(uint32_t dst, const CUtensorMap* m, uint32_t bar, int c0, int c1, int c2) {
    asm volatile("cp.async.bulk.tensor.3d.shared::cluster.global.mbarrier::complete_tx::bytes [%0], [%1, {%3, %4, %5}], [%2];"
                 :: "r"(dst), "l"((uint64_t)m), "r"(bar), "r"(c0), "r"(c1), "r"(c2) : "memory");
}
#define P4 0
#define PROMO CU_TENSOR_MAP_L2_PROMOTION_L2_128B
__device__ __forceinline__ void tma_part(uint32_t dst, const CUtensorMap* m, uint32_t bar, int c0, int c1, int c2) {
    tma_3d(dst, m, bar, c0, c1, c2);
}
__device__ __forceinline__ void bulk_load(uint32_t dst, const void* src, uint32_t bytes, uint32_t bar) {
    asm volatile("cp.async.bulk.shared::cluster.global.mbarrier::complete_tx::bytes [%0], [%1], %2, [%3];"
                 :: "r"(dst), "l"(src), "r"(bytes), "r"(bar) : "memory");
}
__device__ __forceinline__ void bulk_store(void* dst, uint32_t src, uint32_t bytes) {
    asm volatile("cp.async.bulk.global.shared::cta.bulk_group [%0], [%1], %2;" :: "l"(dst), "r"(src), "r"(bytes) : "memory");
}
__device__ __forceinline__ void tma_store_2d(const CUtensorMap* m, uint32_t src, int c0, int c1) {
    asm volatile("cp.async.bulk.tensor.2d.global.shared::cta.bulk_group [%0, {%2, %3}], [%1];"
                 :: "l"((uint64_t)m), "r"(src), "r"(c0), "r"(c1) : "memory");
}
__device__ __forceinline__ void prefetch_map(const CUtensorMap* m) {
    asm volatile("prefetch.tensormap [%0];" :: "l"((uint64_t)m) : "memory");
}
__device__ __forceinline__ void prefetch_l2(const void* p, uint32_t bytes) {
    asm volatile("cp.async.bulk.prefetch.L2.global [%0], %1;" :: "l"(p), "r"(bytes) : "memory");
}
__device__ __forceinline__ void bulk_commit() { asm volatile("cp.async.bulk.commit_group;" ::: "memory"); }
__device__ __forceinline__ void fence_async_smem() { asm volatile("fence.proxy.async.shared::cta;" ::: "memory"); }
__device__ __forceinline__ void wg_fence() { asm volatile("wgmma.fence.sync.aligned;" ::: "memory"); }
__device__ __forceinline__ void wg_commit() { asm volatile("wgmma.commit_group.sync.aligned;" ::: "memory"); }
template <int N> __device__ __forceinline__ void wg_wait() { asm volatile("wgmma.wait_group.sync.aligned %0;" :: "n"(N) : "memory"); }

constexpr uint32_t HI_SW = (1u << 30) | 64u, HI_H = 16u;
__host__ __device__ constexpr uint32_t desc_lo(uint32_t addr, uint32_t lbo) { return (addr >> 4) | ((lbo >> 4) << 16); }

#define R8(a, o) "+f"(a[o + 0]), "+f"(a[o + 1]), "+f"(a[o + 2]), "+f"(a[o + 3]), "+f"(a[o + 4]), "+f"(a[o + 5]), "+f"(a[o + 6]), "+f"(a[o + 7])
#define R32(a, o) R8(a, o), R8(a, o + 8), R8(a, o + 16), R8(a, o + 24)

template <uint32_t HA, int O = 0, int N>
__device__ __forceinline__ void wgmma_n256(float (&d)[N], uint32_t da, uint32_t db, int scale_d) {
    asm volatile("{\n.reg .pred p;\n.reg .b64 da, db;\nsetp.ne.b32 p, %130, 0;\nmov.b64 da, {%128, %131};\nmov.b64 db, {%129, %132};\n"
        "wgmma.mma_async.sync.aligned.m64n256k16.f32.bf16.bf16 "
        "{%0,%1,%2,%3,%4,%5,%6,%7,%8,%9,%10,%11,%12,%13,%14,%15,%16,%17,%18,%19,%20,%21,%22,%23,%24,%25,%26,%27,%28,%29,%30,%31,"
        "%32,%33,%34,%35,%36,%37,%38,%39,%40,%41,%42,%43,%44,%45,%46,%47,%48,%49,%50,%51,%52,%53,%54,%55,%56,%57,%58,%59,%60,%61,%62,%63,"
        "%64,%65,%66,%67,%68,%69,%70,%71,%72,%73,%74,%75,%76,%77,%78,%79,%80,%81,%82,%83,%84,%85,%86,%87,%88,%89,%90,%91,%92,%93,%94,%95,"
        "%96,%97,%98,%99,%100,%101,%102,%103,%104,%105,%106,%107,%108,%109,%110,%111,%112,%113,%114,%115,%116,%117,%118,%119,%120,%121,%122,%123,%124,%125,%126,%127},"
        " da, db, p, 1, 1, 0, 1;\n}\n"
        : R32(d, O + 0), R32(d, O + 32), R32(d, O + 64), R32(d, O + 96)
        : "r"(da), "r"(db), "r"(scale_d), "n"(HA), "n"(HI_SW));
}
template <uint32_t HA, int O = 0, int N>
__device__ __forceinline__ void wgmma_n176(float (&d)[N], uint32_t da, uint32_t db, int scale_d) {
    asm volatile("{\n.reg .pred p;\n.reg .b64 da, db;\nsetp.ne.b32 p, %90, 0;\nmov.b64 da, {%88, %91};\nmov.b64 db, {%89, %92};\n"
        "wgmma.mma_async.sync.aligned.m64n176k16.f32.bf16.bf16 "
        "{%0,%1,%2,%3,%4,%5,%6,%7,%8,%9,%10,%11,%12,%13,%14,%15,%16,%17,%18,%19,%20,%21,%22,%23,%24,%25,%26,%27,%28,%29,%30,%31,"
        "%32,%33,%34,%35,%36,%37,%38,%39,%40,%41,%42,%43,%44,%45,%46,%47,%48,%49,%50,%51,%52,%53,%54,%55,%56,%57,%58,%59,%60,%61,%62,%63,"
        "%64,%65,%66,%67,%68,%69,%70,%71,%72,%73,%74,%75,%76,%77,%78,%79,%80,%81,%82,%83,%84,%85,%86,%87},"
        " da, db, p, 1, 1, 0, 1;\n}\n"
        : R32(d, O + 0), R32(d, O + 32), R8(d, O + 64), R8(d, O + 72), R8(d, O + 80)
        : "r"(da), "r"(db), "r"(scale_d), "n"(HA), "n"(HI_SW));
}
template <uint32_t HA, int O = 0, int N>
__device__ __forceinline__ void wgmma_n128(float (&d)[N], uint32_t da, uint32_t db, int scale_d) {
    asm volatile("{\n.reg .pred p;\n.reg .b64 da, db;\nsetp.ne.b32 p, %66, 0;\nmov.b64 da, {%64, %67};\nmov.b64 db, {%65, %68};\n"
        "wgmma.mma_async.sync.aligned.m64n128k16.f32.bf16.bf16 "
        "{%0,%1,%2,%3,%4,%5,%6,%7,%8,%9,%10,%11,%12,%13,%14,%15,%16,%17,%18,%19,%20,%21,%22,%23,%24,%25,%26,%27,%28,%29,%30,%31,"
        "%32,%33,%34,%35,%36,%37,%38,%39,%40,%41,%42,%43,%44,%45,%46,%47,%48,%49,%50,%51,%52,%53,%54,%55,%56,%57,%58,%59,%60,%61,%62,%63},"
        " da, db, p, 1, 1, 0, 1;\n}\n"
        : R32(d, O + 0), R32(d, O + 32)
        : "r"(da), "r"(db), "r"(scale_d), "n"(HA), "n"(HI_SW));
}
template <int M, int N> __device__ __forceinline__ void fence_regs(float (&d)[N]) {
#pragma unroll
    for (int i = 0; i < M; i++) asm volatile("" : "+f"(d[i]) :: "memory");
}

__device__ __forceinline__ uint32_t pack_bf16(float lo, float hi) {
    uint32_t r;
    asm("cvt.rn.bf16x2.f32 %0, %1, %2;" : "=r"(r) : "f"(hi), "f"(lo));
    return r;
}
__device__ __forceinline__ float gelu_gate(float g) {
    const float K0 = -2.3022081986f;
    const float K1 = -0.1029432397f;
    float t = g * fmaf(g * g, K1, K0);
    float e, r;
    asm("ex2.approx.ftz.f32 %0, %1;" : "=f"(e) : "f"(t));
    asm("rcp.approx.ftz.f32 %0, %1;" : "=f"(r) : "f"(1.0f + e));
    return r;
}
__device__ __forceinline__ float geglu(float g, float u) { return (g * u) * gelu_gate(g); }
__device__ __forceinline__ uint32_t gelu2(float lo, float hi) { return pack_bf16(lo * gelu_gate(lo), hi * gelu_gate(hi)); }
__device__ __forceinline__ uint32_t mul_bf16x2(uint32_t a, uint32_t b) {
    uint32_t r;
    asm("mul.rn.bf16x2 %0, %1, %2;" : "=r"(r) : "r"(a), "r"(b));
    return r;
}
__device__ __forceinline__ uint32_t geglu2(uint32_t g, uint32_t u) {
    float lo = geglu(__uint_as_float(g << 16), __uint_as_float(u << 16));
    float hi = geglu(__uint_as_float(g & 0xffff0000u), __uint_as_float(u & 0xffff0000u));
    return pack_bf16(lo, hi);
}
__device__ __forceinline__ void stsm_x4(uint32_t addr, uint32_t r0, uint32_t r1, uint32_t r2, uint32_t r3) {
    asm volatile("stmatrix.sync.aligned.m8n8.x4.shared.b16 [%0], {%1, %2, %3, %4};"
                 :: "r"(addr), "r"(r0), "r"(r1), "r"(r2), "r"(r3) : "memory");
}

#define PF0 8
#define PF1 4
#define PF2 20
#define PACE0 300
#define PACE1 300
#define PACE2 0
#define POLL 200
#define ORD 1
#define BS 3
#define NP 1
#define CP 0
#define EB 0
#define SMR 1
#define XD 2000
constexpr int TN = 5;
struct Maps { CUtensorMap x64, g16, gp16, w64[2], part[2], x128, d, out; };
struct Ptrs { const uint8_t *wg, *wu, *wd; uint8_t* o; int threads; };

struct Consumer {
    uint32_t st_h;
    int lane, wg;
    mutable int tl = 0;

    __device__ __forceinline__ void release(int bar_idx) const {
        if (lane == 0) mbar_arrive(bars + 8 * bar_idx);
    }
    __device__ __forceinline__ void wait_full(int bar_idx, uint32_t parity) const { mbar_wait(bars + 8 * bar_idx, parity); }
    __device__ __forceinline__ void stage(int c, uint32_t parity, uint32_t r0, uint32_t r1, uint32_t r2, uint32_t r3) const {
        if ((c & 3) == 0) mbar_wait(bars + 8 * (BAR_SEMPTY + 2 * wg + (c >> 2)), parity);
        stsm_x4(st_h + c * 2048, r0, r1, r2, r3);
    }
    __device__ __forceinline__ void publish(int block) const {
        fence_async_smem();
        __syncwarp();
        release(BAR_SFULL + 2 * wg + block);
    }
    __device__ __forceinline__ void stage_geglu(int c, uint32_t parity, const uint32_t (&pk)[64]) const {
        const int q = 4 * c;
        stage(c, parity, geglu2(pk[q], pk[32 + q]), geglu2(pk[q + 1], pk[33 + q]), geglu2(pk[q + 2], pk[34 + q]), geglu2(pk[q + 3], pk[35 + q]));
        if ((c & 3) == 3) publish(c >> 2);
    }
    __device__ __forceinline__ void mma_a(float (&acc)[128], int s, bool first = false) const {
        TL(wg, tl++, (threadIdx.x & 127) == 0);
        const uint32_t da = desc_lo(base, 16) + s * 3072 + wg * 512, db = desc_lo(base + 16384, 8192) + s * 3072;
        wg_fence();
        wgmma_n256<HI_SW>(acc, da, db, first ? 0 : 1);
        wgmma_n256<HI_SW>(acc, da + 2, db + 128, 1);
        wgmma_n256<HI_SW>(acc, da + 4, db + 256, 1);
        wgmma_n256<HI_SW>(acc, da + 6, db + 384, 1);
        wg_commit();
    }
    __device__ __forceinline__ void mma_c(float (&acc)[88], int s, int up, bool first = false) const {
        TL(wg, tl++, (threadIdx.x & 127) == 0);
        const uint32_t da = desc_lo(base + 49152, 16) + s * 4096 + wg * 512, db = desc_lo(base, 8192) + up * 1536 + s * 4096;
        wg_fence();
        wgmma_n176<HI_SW>(acc, da, db, first ? 0 : 1);
        wgmma_n176<HI_SW>(acc, da + 2, db + 128, 1);
        wgmma_n176<HI_SW>(acc, da + 4, db + 256, 1);
        wgmma_n176<HI_SW>(acc, da + 6, db + 384, 1);
        wg_commit();
    }
    __device__ __forceinline__ void mma_b(float (&acc)[64], int s, bool first = false) const {
        TL(wg, tl++, (threadIdx.x & 127) == 0);
        const uint32_t da = desc_lo(base + 16384, 128) + s * 2048 + wg * 128, db = desc_lo(base, 8192) + s * 2048;
        wg_fence();
        wgmma_n128<HI_H>(acc, da, db, first ? 0 : 1);
        wgmma_n128<HI_H>(acc, da + 256, db + 128, 1);
        wgmma_n128<HI_H>(acc, da + 512, db + 256, 1);
        wgmma_n128<HI_H>(acc, da + 768, db + 384, 1);
        wg_commit();
    }
    __device__ __forceinline__ void step_a(float (&acc)[128], int kb) const {
        mma_a(acc, kb & 3);
        release(BAR_EMPTY_A + ((kb - 1) & 3));
    }
    __device__ __forceinline__ void next_a(int kb) const { wait_full(BAR_FULL_A + ((kb + 1) & 3), ((kb + 1) >> 2) & 1); }
};

__global__ void __launch_bounds__(NUM_THREADS, 1) geglu_ffn_kernel(const Ptrs pp, const __grid_constant__ Maps mp) {
    extern __shared__ __align__(1024) uint8_t smem_raw[];
    const int warp = __shfl_sync(0xffffffffu, threadIdx.x >> 5, 0);
    const int lane = threadIdx.x & 31;

    uint32_t sm;
    asm("mov.u32 %0, %%smid;" : "=r"(sm));
    const int tpc = sm >> 1;
    const int q7 = ((tpc - 32) * 37) >> 8;
    const bool extra = (tpc >> 1) == 30;
    const int grp = tpc < 32 ? tpc & 7 : tpc < 60 ? tpc - 31 - 7 * q7 : 0;
    const int j_blk = tpc < 32 ? tpc >> 3 : tpc < 60 ? 4 + q7 : tpc - 58;
    const int m_blk = extra ? (sm & 3) * 4 : grp * 2 + (sm & 1);
    const int col0 = extra ? 54 : j_blk * 2;

    const uint32_t full_c = bars + 8 * BAR_FULL_C, piece = bars + 8 * BAR_PIECE;
    if (!SMR && warp >= 8) asm volatile("setmaxnreg.dec.sync.aligned.u32 24;");
    if (warp == 8) {
        if (!extra && elect_one()) {
            const uint32_t b = base + 2 * 65536;
            mbar_init(piece, 1);
            mbar_init(piece + 8, 1);
            mbar_init(piece + 16, 1);
            mbar_init(full_c + 32, 1);
            mbar_init(full_c + 40, 1);
            asm volatile("fence.mbarrier_init.release.cluster;" ::: "memory");
            TL(2, 0, true);
            mbar_expect_tx(piece, 8192 + 6144);
            tma_2d(b + 49152, &mp.x64, piece, 0, m_blk * 128);
            tma_3d(b, &mp.g16, piece, 0, 0, col0);
            tma_part(b + 4096, &mp.gp16, piece, 0, 0, j_blk);
            mbar_expect_tx(piece + 8, 8192);
            tma_2d(b + 57344, &mp.x64, piece + 8, 0, m_blk * 128 + 64);
            mbar_expect_tx(piece + 16, 6144);
            tma_3d(b + 6144, &mp.g16, piece + 16, 0, 16, col0);
            tma_part(b + 10240, &mp.gp16, piece + 16, 0, 16, j_blk);
            mbar_expect_tx(full_c + 32, 12288);
            tma_3d(b + 12288, &mp.g16, full_c + 32, 0, 32, col0);
            tma_part(b + 16384, &mp.gp16, full_c + 32, 0, 32, j_blk);
            tma_3d(b + 18432, &mp.g16, full_c + 32, 0, 48, col0);
            tma_part(b + 22528, &mp.gp16, full_c + 32, 0, 48, j_blk);
            TL(2, 1, true);
            mbar_expect_tx(full_c + 40, 24576);
            tma_3d(b + 24576, &mp.w64[1], full_c + 40, 0, 0, col0);
            tma_part(b + 40960, &mp.part[1], full_c + 40, 0, 0, j_blk);
            TL(2, 121, true);
#pragma unroll
            for (int i = 0; i < 4; i++) mbar_init(full_c + 8 * i, 1);
#pragma unroll
            for (int i = 0; i < 6; i++) mbar_init(bars + 8 * (BAR_EMPTY_C + i), 8);
            asm volatile("fence.mbarrier_init.release.cluster;" ::: "memory");
            if (EB == 1) {
                TL(2, 2, true);
                mbar_expect_tx(full_c, 40960);
                tma_2d(base + 49152, &mp.x128, full_c, 64, m_blk * 128);
                tma_3d(base, &mp.w64[0], full_c, 0, 64, col0);
                tma_part(base + 16384, &mp.part[0], full_c, 0, 64, j_blk);
            }
        }
        __syncwarp();
        asm volatile("bar.arrive 4, 384;" ::: "memory");
    } else {
        asm volatile("bar.sync 4, %0;" :: "r"(CP ? pp.threads : 384) : "memory");
        asm volatile("nanosleep.u32 0;" ::: "memory");
    }

    if (warp < 8) {
        TL(0, 121, threadIdx.x == 0);
        if (warp == 0) {
            if (elect_one()) {
#pragma unroll
                for (int i = 0; i < BAR_FULL_C; i++) {
                    const bool empty = (i >= BAR_EMPTY_A && i < BAR_FULL_B) || (i >= BAR_EMPTY_B && i < BAR_SFULL);
                    mbar_init(bars + 8 * i, empty ? 8 : (i >= BAR_SFULL && i < BAR_SEMPTY) ? 4 : 1);
                }
                asm volatile("fence.mbarrier_init.release.cluster;" ::: "memory");
            }
            __syncwarp();
            asm volatile("bar.arrive 2, %0;" :: "r"(extra ? 160 : 128) : "memory");
        }
        asm volatile("setmaxnreg.inc.sync.aligned.u32 240;");
        TL(0, 123, threadIdx.x == 0);
        asm volatile("bar.sync 1, 256;" ::: "memory");
        TL(0, 122, threadIdx.x == 0);
        Consumer c;
        c.lane = lane;
        c.wg = warp >> 2;
        c.st_h = base + STAGING_OFF + c.wg * 16384 + (warp & 3) * 512 + (lane & 8) * 32 + (lane >> 4) * 128 + (lane & 7) * 16;
        const bool always = sm != 0xffffffffu;

        uint32_t pk[64], gp[12], up[12];
        if (extra) {
#pragma unroll
            for (int i = 4 * NP; i < 12; i++) asm volatile("" : "=r"(gp[i]), "=r"(up[i]));
#pragma unroll
            for (int i = 0; i < 64; i++) asm volatile("" : "=r"(pk[i]));
            c.wait_full(BAR_FULL_A, 0);
        } else {
            float accg[88], accu[88];
#pragma unroll
            for (int i = 0; i < 88; i++) asm volatile("" : "=f"(accg[i]), "=f"(accu[i]));
            const uint32_t da = desc_lo(base + 2 * 65536 + 49152, 16) + c.wg * 512;
            constexpr uint32_t dq = desc_lo(base + 2 * 65536, 2048);
            c.wait_full(BAR_PIECE + c.wg, 0);
            c.wait_full(BAR_PIECE, 0);
            TL(0, 124, threadIdx.x == 0);
            TL(c.wg, c.tl++, (threadIdx.x & 127) == 0);
            wg_fence();
            wgmma_n176<HI_SW>(accg, da, dq, 0);
            TS(1, threadIdx.x == 0);
            c.wait_full(BAR_PIECE + 2, 0);
            wg_fence();
            wgmma_n176<HI_SW>(accg, da + 2, dq + 384, 1);
            c.wait_full(BAR_FULL_C + 4, 0);
            wg_fence();
            wgmma_n176<HI_SW>(accg, da + 4, dq + 768, 1);
            wgmma_n176<HI_SW>(accg, da + 6, dq + 1152, 1);
            wg_commit();
            c.wait_full(BAR_FULL_C + 5, 0);
            if (ORD && c.wg) asm volatile("bar.sync 6, 256;" ::: "memory");
            c.mma_c(accu, 2, 1, true);
            if (ORD && !c.wg) asm volatile("bar.arrive 6, 256;" ::: "memory");
            wg_wait<1>();
            c.release(BAR_EMPTY_C + 4);
            c.wait_full(BAR_FULL_C, 0);
            int s = 0, ps = 2;
            uint32_t ph = 0;
#pragma unroll 1
            for (int kb = 1; kb < 15; kb++) {
                wg_wait<0>();
                c.mma_c(accg, s, 0);
                c.release(BAR_EMPTY_C + 2 * ps + 1);
                c.wait_full(BAR_FULL_C + 2 * s + 1, ph);
                wg_wait<0>();
                c.mma_c(accu, s, 1);
                c.release(BAR_EMPTY_C + 2 * s);
                ps = s;
                if (++s == 3) s = 0;
                if (s == 2) ph ^= 1;
                c.wait_full(BAR_FULL_C + 2 * s, ph);
            }
            wg_wait<0>();
            c.mma_c(accg, 2, 0);
            c.release(BAR_EMPTY_C + 3);
            c.wait_full(BAR_FULL_C + 5, 1);
            c.mma_c(accu, 2, 1);
            wg_wait<1>();
            fence_regs<88>(accg);
            c.release(BAR_EMPTY_C + 4);
#pragma unroll
            for (int i = 0; i < 32; i++) asm volatile("" : "=r"(pk[i]));
#pragma unroll
            for (int i = 0; i < 12; i++) asm volatile("" : "=r"(gp[i]));
            if (always) {
#pragma unroll
                for (int i = 0; i < 12; i++) {
                    gp[i] = i < 4 * NP ? gelu2(accg[64 + 2 * i], accg[65 + 2 * i]) : pack_bf16(accg[64 + 2 * i], accg[65 + 2 * i]);
                    asm volatile("" : "+r"(gp[i]));
                }
#pragma unroll
                for (int i = 0; i < 32; i++) {
                    pk[i] = pack_bf16(accg[2 * i], accg[2 * i + 1]);
                    asm volatile("" : "+r"(pk[i]));
                }
            }
            c.wait_full(BAR_FULL_A, 0);
            wg_wait<0>();
            fence_regs<88>(accu);
            c.release(BAR_EMPTY_C + 5);
#pragma unroll
            for (int i = 0; i < 12; i++) up[i] = pack_bf16(accu[64 + 2 * i], accu[65 + 2 * i]);
#pragma unroll
            for (int i = 0; i < 4 * NP; i += 4)
                stsm_x4(c.st_h + 8192 + i * 512, mul_bf16x2(gp[i], up[i]), mul_bf16x2(gp[i + 1], up[i + 1]),
                        mul_bf16x2(gp[i + 2], up[i + 2]), mul_bf16x2(gp[i + 3], up[i + 3]));
#pragma unroll
            for (int i = 0; i < 32; i++) pk[32 + i] = pack_bf16(accu[2 * i], accu[2 * i + 1]);
            TS(2, threadIdx.x == 0);
        }

        float acc[128];
#pragma unroll
        for (int i = 0; i < 128; i++) asm volatile("" : "=f"(acc[i]));
        auto stage_part = [&](int i) {
            stsm_x4(c.st_h + 8192 + i * 512, geglu2(gp[i], up[i]), geglu2(gp[i + 1], up[i + 1]), geglu2(gp[i + 2], up[i + 2]), geglu2(gp[i + 3], up[i + 3]));
        };
        c.mma_a(acc, 0, true);
        c.wait_full(BAR_FULL_A + 1, 0);
        c.mma_a(acc, 1);
        if (!extra) stage_part(4 * NP);
        wg_wait<1>();
        c.release(BAR_EMPTY_A);
        if (!extra) {
#pragma unroll
            for (int i = 4 * NP + 4; i < 12; i += 4) stage_part(i);
            c.publish(1);
        }
        c.wait_full(BAR_FULL_A + 2, 0);
#pragma unroll 1
        for (int t = extra ? 0 : 2;; t++) {
#pragma unroll
            for (int kb = 2; kb < 10; kb++) {
                wg_wait<0>();
                c.step_a(acc, kb);
                if (t > 0) c.stage_geglu(kb - 2, t & 1, pk);
                c.next_a(kb);
            }
#pragma unroll 1
            for (int kb = 10; kb < 15; kb++) {
                wg_wait<0>();
                c.step_a(acc, kb);
                c.next_a(kb);
            }
            if (t == 3) break;
            c.mma_a(acc, 3);
            wg_wait<1>();
            c.release(BAR_EMPTY_A + 2);
            c.wait_full(BAR_FULL_A, 0);
            wg_wait<0>();
            fence_regs<128>(acc);
            c.release(BAR_EMPTY_A + 3);
#pragma unroll
            for (int i = 0; i < 64; i++) pk[i] = pack_bf16(acc[2 * i], acc[2 * i + 1]);
            TS(3, threadIdx.x == 0);
            c.mma_a(acc, 0, true);
            c.wait_full(BAR_FULL_A + 1, 0);
            c.mma_a(acc, 1);
            wg_wait<1>();
            c.release(BAR_EMPTY_A);
            c.wait_full(BAR_FULL_A + 2, 0);
        }
        wg_wait<0>();
        c.step_a(acc, 15);
        auto stage_acc = [&](int q) {
            const int g = 8 * q, u = 64 + 8 * q;
            c.stage(q, 0, pack_bf16(geglu(acc[g], acc[u]), geglu(acc[g + 1], acc[u + 1])), pack_bf16(geglu(acc[g + 2], acc[u + 2]), geglu(acc[g + 3], acc[u + 3])),
                    pack_bf16(geglu(acc[g + 4], acc[u + 4]), geglu(acc[g + 5], acc[u + 5])), pack_bf16(geglu(acc[g + 6], acc[u + 6]), geglu(acc[g + 7], acc[u + 7])));
        };
        if (extra) {
            wg_wait<0>();
            fence_regs<128>(acc);
#pragma unroll
            for (int q = 0; q < 8; q++) {
                stage_acc(q);
                if ((q & 3) == 3) c.publish(q >> 2);
            }
            TS(7, threadIdx.x == 0);
            TL(c.wg, 126, (threadIdx.x & 127) == 0);
            TL_DUMP();
            return;
        }
        c.wait_full(BAR_FULL_B, 0);
        TS(5, threadIdx.x == 0);

        constexpr int KB0 = BS == 0 ? 8 : BS == 1 ? 10 : BS == 2 ? 16 : 17;
        float acc4[64];
        uint32_t h0, h1;
#pragma unroll
        for (int kb = 0; kb < KB0; kb++) {
            wg_wait<0>();
            if (kb == 0) fence_regs<128>(acc);
            c.mma_b(acc4, kb % STB, kb == 0);
            c.release(kb == 0 ? BAR_EMPTY_A + 3 : BAR_EMPTY_B + (kb - 1) % STB);
            if (BS >= 2 && !(kb & 1)) asm volatile("" : "=r"(h0), "=r"(h1));
            if (always) {
                if (BS == 0) {
                    stage_acc(kb);
                    if ((kb & 3) == 3) c.publish(kb >> 2);
                } else if (BS == 1) {
                    if (kb % 5 == 4) c.publish(kb / 5);
                    else stage_acc(kb - kb / 5);
                } else {
                    if (BS == 3 && kb % 8 == 0 && kb) c.publish(kb / 8 - 1);
                    if (kb < 16) {
                        const int g = 4 * kb, u = 64 + g;
                        const uint32_t r0 = pack_bf16(geglu(acc[g], acc[u]), geglu(acc[g + 1], acc[u + 1]));
                        const uint32_t r1 = pack_bf16(geglu(acc[g + 2], acc[u + 2]), geglu(acc[g + 3], acc[u + 3]));
                        if (kb & 1) {
                            c.stage(kb >> 1, 0, h0, h1, r0, r1);
                        } else {
                            h0 = r0;
                            h1 = r1;
                            asm volatile("" : "+r"(h0), "+r"(h1));
                        }
                    }
                    if (BS == 2 && kb % 8 == 7) c.publish(kb / 8);
                }
            }
            c.wait_full(BAR_FULL_B + (kb + 1) % STB, ((kb + 1) / STB) & 1);
        }
        int s = KB0 % STB, ps = (KB0 - 1) % STB;
        uint32_t ph = (KB0 / STB) & 1;
#pragma unroll 1
        for (int kb = KB0; kb < KB_FF - TN; kb++) {
            wg_wait<0>();
            c.mma_b(acc4, s);
            c.release(BAR_EMPTY_B + ps);
            ps = s;
            if (++s == STB) { s = 0; ph ^= 1; }
            c.wait_full(BAR_FULL_B + s, ph);
        }
        c.wait_full(BAR_SEMPTY + 2 * c.wg, 1);
        c.wait_full(BAR_SEMPTY + 2 * c.wg + 1, 1);
        const uint32_t strip = base + STAGING_OFF + c.wg * 16384 + (warp & 3) * 2048;
        const uint32_t st_row = strip + (lane & 15) * 128, st_sw = ((lane >> 4) ^ (lane & 7)) << 4;
        const int row0 = m_blk * 128 + warp * 16;
        const uint32_t ld_row = strip + (lane >> 3) * 128 + (((lane & 7) ^ (lane >> 3)) << 4);
        uint8_t* optr = pp.o + (size_t)(row0 + (lane >> 3)) * 2048 + j_blk * 256 + (lane & 7) * 16;
        if (c.wg) asm volatile("bar.sync 6, 256;" ::: "memory");
#pragma unroll
        for (int kb = KB_FF - TN; kb < KB_FF; kb++) {
            if (kb > KB_FF - TN) c.wait_full(BAR_FULL_B + kb % STB, (kb / STB) & 1);
            c.mma_b(acc4, kb % STB);
        }
        if (!c.wg) asm volatile("bar.arrive 6, 256;" ::: "memory");

#pragma unroll
        for (int h = 0; h < 2; h++) {
            if (h == 0) {
                wg_wait<0>();
                fence_regs<64>(acc4);
                TS(6, threadIdx.x == 0);
                TL(c.wg, 125, (threadIdx.x & 127) == 0);
            }
#pragma unroll
            for (int q = 0; q < 4; q++) {
                const int i = 32 * h + 8 * q;
                stsm_x4(st_row + h * 8192 + (st_sw ^ (q << 5)), pack_bf16(acc4[i], acc4[i + 1]), pack_bf16(acc4[i + 2], acc4[i + 3]),
                        pack_bf16(acc4[i + 4], acc4[i + 5]), pack_bf16(acc4[i + 6], acc4[i + 7]));
            }
            if (c.wg) {
                __syncwarp();
                uint4 v[4];
#pragma unroll
                for (int i = 0; i < 4; i++)
                    asm volatile("ld.shared.v4.u32 {%0, %1, %2, %3}, [%4];" : "=r"(v[i].x), "=r"(v[i].y), "=r"(v[i].z), "=r"(v[i].w)
                                 : "r"((ld_row ^ ((i & 1) << 6)) + i * 512 + h * 8192) : "memory");
#pragma unroll
                for (int i = 0; i < 4; i++)
                    asm volatile("st.global.v4.u32 [%0], {%1, %2, %3, %4};" :: "l"(optr + i * 8192 + h * 128), "r"(v[i].x), "r"(v[i].y), "r"(v[i].z), "r"(v[i].w) : "memory");
            } else {
                fence_async_smem();
                __syncwarp();
                if (elect_one()) {
                    tma_store_2d(&mp.out, strip + h * 8192, j_blk * 128 + h * 64, row0);
                    bulk_commit();
                }
            }
        }
        if (elect_one()) asm volatile("cp.async.bulk.wait_group.read 0;" ::: "memory");
        __syncwarp();
        TL(c.wg, 126, (threadIdx.x & 127) == 0);
        TS(7, threadIdx.x == 0);
        TL_DUMP();
    } else {
        if (SMR) asm volatile("setmaxnreg.dec.sync.aligned.u32 24;");
        if (EB >= 2 && warp == 6 + EB && !extra) {
            if (elect_one()) {
                TL(2, 2, true);
                mbar_expect_tx(full_c, 40960);
                tma_2d(base + 49152, &mp.x128, full_c, 64, m_blk * 128);
                tma_3d(base, &mp.w64[0], full_c, 0, 64, col0);
                tma_part(base + 16384, &mp.part[0], full_c, 0, 64, j_blk);
            }
            __syncwarp();
        }
        if (warp != 8) {
            asm volatile("bar.sync 2, %0;" :: "r"(extra ? 160 : 128) : "memory");
            uint32_t cnt;
            if (warp == 11) asm volatile("ld.relaxed.gpu.global.u32 %0, [%1];" : "=r"(cnt) : "l"(g_ready + m_blk * 4) : "memory");
            asm volatile("bar.sync 5, 96;" ::: "memory");
            if (elect_one()) {
                if (warp <= 10) {
                    const int w = warp - 9;
                    if (!extra) mbar_arrive(bars + 8 * (BAR_SEMPTY + 2 * w));
#pragma unroll 1
                    for (int b = extra ? 0 : 1; b < 8; b++) {
                        const int t = b >> 1;
                        const bool part = !extra && b == 1;
                        const int m = extra ? m_blk + t : m_blk;
                        const int chunk = part ? 64 + 3 * j_blk : (col0 + (b & 1) + (extra || t == 1 ? 0 : 16 * t - 10)) * 4;
                        uint8_t* dst = g_h + ((size_t)m * (KB_FF * 4) + chunk) * 4096 + w * 2048;
                        const uint32_t src = base + STAGING_OFF + w * 16384 + (b & 1) * 8192;
                        const uint32_t pace = t < 2 ? PACE0 : t == 2 ? PACE1 : PACE2;
                        mbar_wait_p(bars + 8 * (BAR_SFULL + 2 * w + (b & 1)), (extra ? t : t + b + 1) & 1);
#pragma unroll 1
                        for (int q = 0; q < (part ? 3 : 4); q++) {
                            if (q | (b & 1)) __nanosleep(pace);
                            bulk_store(dst + q * 4096, src + q * 2048, 2048);
                            bulk_commit();
                            asm volatile("cp.async.bulk.wait_group.read 0;" ::: "memory");
                        }
                        mbar_arrive(bars + 8 * (BAR_SEMPTY + 2 * w + (b & 1)));
                        if ((b & 1) && !part) {
                            asm volatile("cp.async.bulk.wait_group 0;" ::: "memory");
                            asm volatile("fence.proxy.async.global;" ::: "memory");
                            asm volatile("red.release.gpu.global.add.u32 [%0], %1;"
                                         :: "l"(g_ready + m * 4 + (extra ? 3 : t - 1)), "r"(extra ? 16 : 2) : "memory");
                        }
                    }
                } else {
                    TS(0, true);
                    uint32_t nsm;
                    asm("mov.u32 %0, %%nsmid;" : "=r"(nsm));
                    if (smem_u32(smem_raw) != base || nsm != NUM_CTAS) __trap();
                    prefetch_map(&mp.d);
                    prefetch_map(&mp.out);
                    if (extra) return;
                    const int row = m_blk * 64 + j_blk * 8;
#pragma unroll 1
                    for (int t = 0; t < 2; t++) {
                        mbar_wait_p(bars + 8 * (BAR_PF + t), 0);
#pragma unroll 1
                        for (int r = row; r < row + 8; r++) {
                            prefetch_l2(pp.wg + r * (D_FF * 2) + 2816 + t * 2048, 2048);
                            prefetch_l2(pp.wu + r * (D_FF * 2) + 2816 + t * 2048, 2048);
                        }
                    }
                    mbar_wait_p(bars + 8 * (BAR_PF + 2), 0);
                    prefetch_l2(pp.wd + row * 2048, 16384);
#pragma unroll 1
                    for (int round = 0; round < 4; round++) {
                        uint32_t v, it = 0;
                        while (true) {
                            asm volatile("ld.acquire.gpu.global.u32 %0, [%1];" : "=r"(v) : "l"(g_ready + m_blk * 4 + round) : "memory");
                            if (v - (cnt & ~31u) >= 32u) break;
                            if (++it > (1u << 20)) __trap();
                            __nanosleep(POLL);
                        }
                        asm volatile("fence.proxy.async.global;" ::: "memory");
                        mbar_arrive(bars + 8 * (BAR_HREADY + round));
                        TL(2, 122 + round, true);
                    }
                }
            }
            return;
        }
        if (extra) asm volatile("bar.sync 2, 160;" ::: "memory");
        if (!elect_one()) return;
        if (XD && extra) __nanosleep(XD);
        if (!extra) {
            int s = EB ? 1 : 0;
            uint32_t ph = 1;
#pragma unroll 1
            for (int i = EB ? 3 : 2; i < 32; i++) {
                const uint32_t full = full_c + 8 * s, b = base + (s >> 1) * 65536, bw = b + (i & 1) * 24576;
                if (s == 4) ph ^= 1;
                mbar_wait_p(bars + 8 * (BAR_EMPTY_C + s), ph);
                TL(2, i, true);
                if ((i & 1) && (!EB || i > 3)) tma_2d(b + 49152, &mp.x128, full - 8, (i >> 1) * 64, m_blk * 128);
                mbar_expect_tx(full, (i & 1) ? 24576 : 40960);
                tma_3d(bw, &mp.w64[i & 1], full, 0, (i >> 1) * 64, col0);
                tma_part(bw + 16384, &mp.part[i & 1], full, 0, (i >> 1) * 64, j_blk);
                if (i == PF0 + ((3 * m_blk) >> 1)) mbar_arrive(bars + 8 * BAR_PF);
                if (++s == 6) s = 0;
            }
        }
#pragma unroll 1
        for (int i = 0; i < (extra ? 64 : 32); i++) {
            const int s = i & 3, k0 = (i & 15) * 64, t = i >> 4;
            const int c0 = extra ? col0 : col0 + 16 * t + 22;
            const uint32_t full = bars + 8 * (BAR_FULL_A + s), b = base + s * 49152;
            if (i < 4 && !extra) mbar_wait_p(bars + 8 * (BAR_EMPTY_C + (i ? i + 2 : 1)), i >> 1);
            else mbar_wait_p(bars + 8 * (BAR_EMPTY_A + s), ((i >> 2) & 1) ^ 1);
            TL(2, extra ? i : 32 + i, true);
            mbar_expect_tx(full, 49152);
            tma_2d(b, &mp.x128, full, k0, (extra ? m_blk + t : m_blk) * 128);
            tma_3d(b + 16384, &mp.w64[0], full, 0, k0, c0);
            tma_3d(b + 32768, &mp.w64[1], full, 0, k0, c0);
            if (i == PF1 + m_blk) mbar_arrive(bars + 8 * (BAR_PF + 1));
            if (i == PF2 + (m_blk >> 1)) mbar_arrive(bars + 8 * (BAR_PF + 2));
        }
        if (extra) return;
        const uint8_t* h_src = g_h + (size_t)m_blk * KB_FF * 16384;
        int s = 0;
        uint32_t ph = 1;
#pragma unroll 1
        for (int i = 0; i < KB_FF; i++) {
            const uint32_t full = bars + 8 * (BAR_FULL_B + s);
            if (i < STB) mbar_wait_p(bars + 8 * (BAR_EMPTY_A + ((2 * i + 1) / 3)), 1);
            else mbar_wait_p(bars + 8 * (BAR_EMPTY_B + s), ph);
            TL(2, 64 + i, true);
            mbar_expect_tx(full, 32768);
            tma_3d(base + s * 32768, &mp.d, full, 0, i * 64, col0);
            if (i == 0 || (i & 15) == 6) mbar_wait_p(bars + 8 * (BAR_HREADY + (i >> 4)), 0);
            bulk_load(base + s * 32768 + 16384, h_src + (size_t)i * 16384, 16384, full);
            if (++s == STB) { s = 0; ph ^= 1; }
        }
    }
}

typedef CUresult (*EncodeFn)(CUtensorMap*, CUtensorMapDataType, cuuint32_t, void*, const cuuint64_t*, const cuuint64_t*,
                             const cuuint32_t*, const cuuint32_t*, CUtensorMapInterleave, CUtensorMapSwizzle,
                             CUtensorMapL2promotion, CUtensorMapFloatOOBfill);

void map_2d(EncodeFn enc, CUtensorMap* m, const void* p, int rows, int cols, int box_rows) {
    cuuint64_t dims[2] = {(cuuint64_t)cols, (cuuint64_t)rows};
    cuuint64_t str[1] = {(cuuint64_t)cols * 2};
    cuuint32_t box[2] = {64, (cuuint32_t)box_rows};
    cuuint32_t es[2] = {1, 1};
    enc(m, CU_TENSOR_MAP_DATA_TYPE_BFLOAT16, 2, const_cast<void*>(p), dims, str, box, es, CU_TENSOR_MAP_INTERLEAVE_NONE,
        CU_TENSOR_MAP_SWIZZLE_128B, CU_TENSOR_MAP_L2_PROMOTION_L2_128B, CU_TENSOR_MAP_FLOAT_OOB_FILL_NONE);
}
void map_w(EncodeFn enc, CUtensorMap* m, const void* p, int K, int N, int rows, int atoms) {
    cuuint64_t dims[3] = {64, (cuuint64_t)K, (cuuint64_t)N / 64};
    cuuint64_t str[2] = {(cuuint64_t)N * 2, 128};
    cuuint32_t box[3] = {64, (cuuint32_t)rows, (cuuint32_t)atoms};
    cuuint32_t es[3] = {1, 1, 1};
    enc(m, CU_TENSOR_MAP_DATA_TYPE_BFLOAT16, 3, const_cast<void*>(p), dims, str, box, es, CU_TENSOR_MAP_INTERLEAVE_NONE,
        CU_TENSOR_MAP_SWIZZLE_128B, CU_TENSOR_MAP_L2_PROMOTION_L2_128B, CU_TENSOR_MAP_FLOAT_OOB_FILL_NONE);
}

void map_part(EncodeFn enc, CUtensorMap* m, const void* p, int rows) {
    cuuint64_t dims[3] = {48, (cuuint64_t)D_MODEL, 8};
    cuuint64_t str[2] = {(cuuint64_t)D_FF * 2, 96};
    cuuint32_t box[3] = {64, (cuuint32_t)rows, 1};
    cuuint32_t es[3] = {1, 1, 1};
    enc(m, CU_TENSOR_MAP_DATA_TYPE_BFLOAT16, 3, (char*)const_cast<void*>(p) + 1024 * 2, dims, str, box, es, CU_TENSOR_MAP_INTERLEAVE_NONE,
        CU_TENSOR_MAP_SWIZZLE_128B, PROMO, CU_TENSOR_MAP_FLOAT_OOB_FILL_NONE);
}

}

extern "C" void kernel_launch(void* const* d_in, const int* in_sizes, int n_in, void* d_out, int out_size) {
    (void)in_sizes; (void)n_in; (void)out_size;
    void* fn = nullptr;
    cudaDriverEntryPointQueryResult st;
    cudaGetDriverEntryPoint("cuTensorMapEncodeTiled", &fn, cudaEnableDefault, &st);
    EncodeFn enc = (EncodeFn)fn;
    Maps mp;
    map_2d(enc, &mp.x64, d_in[0], M_TOK, D_MODEL, 64);
    map_2d(enc, &mp.x128, d_in[0], M_TOK, D_MODEL, 128);
    map_w(enc, &mp.g16, d_in[1], D_MODEL, D_FF, 16, 2);
    map_part(enc, &mp.gp16, d_in[1], 16);
    map_w(enc, &mp.w64[0], d_in[1], D_MODEL, D_FF, 64, 2);
    map_w(enc, &mp.w64[1], d_in[2], D_MODEL, D_FF, 64, 2);
    map_part(enc, &mp.part[0], d_in[1], 64);
    map_part(enc, &mp.part[1], d_in[2], 64);
    map_w(enc, &mp.d, d_in[3], D_FF, D_MODEL, 64, 2);
    map_2d(enc, &mp.out, d_out, M_TOK, D_MODEL, 16);
    const Ptrs pp = {(const uint8_t*)d_in[1], (const uint8_t*)d_in[2], (const uint8_t*)d_in[3], (uint8_t*)d_out, NUM_THREADS};
    cudaFuncSetAttribute(geglu_ffn_kernel, cudaFuncAttributeMaxDynamicSharedMemorySize, SMEM_BYTES);
    geglu_ffn_kernel<<<NUM_CTAS, NUM_THREADS, SMEM_BYTES>>>(pp, mp);
}
```

```cpp
#include <cuda_runtime.h>
#include <cuda_bf16.h>
#include <cuda.h>
#include <stdint.h>

namespace {

constexpr int M_TOK = 2048, D_MODEL = 1024, D_FF = 3584;
constexpr int KB_FF = D_FF / 64;
constexpr int NUM_CTAS = 132;
constexpr int NUM_THREADS = 384;

constexpr int STB = 6;
constexpr int RING_BYTES = 196608;
constexpr int STAGING_OFF = RING_BYTES;
constexpr int BAR_OFF = STAGING_OFF + 32768;
constexpr int SMEM_BYTES = BAR_OFF + 512;
constexpr uint32_t base = 1024, bars = base + BAR_OFF;

constexpr int BAR_FULL_A = 0, BAR_EMPTY_A = 4, BAR_FULL_B = 8, BAR_EMPTY_B = 14, BAR_SFULL = 20, BAR_SEMPTY = 24,
              BAR_HREADY = 28, BAR_PF = 32, BAR_FULL_C = 35, BAR_EMPTY_C = 41, BAR_PIECE = 47;

__device__ __align__(1024) uint8_t g_h[(size_t)M_TOK * D_FF * 2];
__device__ __align__(16) unsigned int g_ready[16 * 4];

__device__ __forceinline__ uint32_t smem_u32(const void* p) { return (uint32_t)__cvta_generic_to_shared(p); }
__device__ __forceinline__ bool elect_one() {
    uint32_t p;
    asm volatile("{\n.reg .pred p;\nelect.sync _|p, 0xffffffff;\nselp.u32 %0, 1, 0, p;\n}" : "=r"(p));
    return p != 0;
}
__device__ __forceinline__ void mbar_init(uint32_t bar, uint32_t cnt) {
    asm volatile("mbarrier.init.shared::cta.b64 [%0], %1;" :: "r"(bar), "r"(cnt) : "memory");
}
__device__ __forceinline__ void mbar_expect_tx(uint32_t bar, uint32_t bytes) {
    asm volatile("mbarrier.arrive.expect_tx.shared::cta.b64 _, [%0], %1;" :: "r"(bar), "r"(bytes) : "memory");
}
__device__ __forceinline__ void mbar_arrive(uint32_t bar) {
    asm volatile("mbarrier.arrive.shared::cta.b64 _, [%0];" :: "r"(bar) : "memory");
}
__device__ __forceinline__ bool mbar_try(uint32_t bar, uint32_t parity) {
    uint32_t done;
    asm volatile("{\n.reg .pred p;\nmbarrier.try_wait.parity.shared::cta.b64 p, [%1], %2;\nselp.u32 %0, 1, 0, p;\n}"
                 : "=r"(done) : "r"(bar), "r"(parity) : "memory");
    return done != 0;
}
__device__ __forceinline__ void mbar_wait_p(uint32_t bar, uint32_t parity) {
    uint32_t it = 0;
#pragma unroll 1
    while (!mbar_try(bar, parity)) {
        if (++it > (1u << 20)) __trap();
    }
}
__device__ __forceinline__ void mbar_wait(uint32_t bar, uint32_t parity) {
    if (mbar_try(bar, parity)) return;
    uint32_t it = 0;
#pragma unroll 1
    while (!mbar_try(bar, parity)) {
        if (++it > (1u << 21)) break;
    }
}
__device__ __forceinline__ void tma_2d(uint32_t dst, const CUtensorMap* m, uint32_t bar, int c0, int c1) {
    asm volatile("cp.async.bulk.tensor.2d.shared::cluster.global.mbarrier::complete_tx::bytes [%0], [%1, {%3, %4}], [%2];"
                 :: "r"(dst), "l"((uint64_t)m), "r"(bar), "r"(c0), "r"(c1) : "memory");
}
__device__ __forceinline__ void tma_3d(uint32_t dst, const CUtensorMap* m, uint32_t bar, int c0, int c1, int c2) {
    asm volatile("cp.async.bulk.tensor.3d.shared::cluster.global.mbarrier::complete_tx::bytes [%0], [%1, {%3, %4, %5}], [%2];"
                 :: "r"(dst), "l"((uint64_t)m), "r"(bar), "r"(c0), "r"(c1), "r"(c2) : "memory");
}
__device__ __forceinline__ void bulk_load(uint32_t dst, const void* src, uint32_t bytes, uint32_t bar) {
    asm volatile("cp.async.bulk.shared::cluster.global.mbarrier::complete_tx::bytes [%0], [%1], %2, [%3];"
                 :: "r"(dst), "l"(src), "r"(bytes), "r"(bar) : "memory");
}
__device__ __forceinline__ void bulk_store(void* dst, uint32_t src, uint32_t bytes) {
    asm volatile("cp.async.bulk.global.shared::cta.bulk_group [%0], [%1], %2;" :: "l"(dst), "r"(src), "r"(bytes) : "memory");
}
__device__ __forceinline__ void tma_store_2d(const CUtensorMap* m, uint32_t src, int c0, int c1) {
    asm volatile("cp.async.bulk.tensor.2d.global.shared::cta.bulk_group [%0, {%2, %3}], [%1];"
                 :: "l"((uint64_t)m), "r"(src), "r"(c0), "r"(c1) : "memory");
}
__device__ __forceinline__ void prefetch_map(const CUtensorMap* m) {
    asm volatile("prefetch.tensormap [%0];" :: "l"((uint64_t)m) : "memory");
}
__device__ __forceinline__ void prefetch_l2(const void* p, uint32_t bytes) {
    asm volatile("cp.async.bulk.prefetch.L2.global [%0], %1;" :: "l"(p), "r"(bytes) : "memory");
}
__device__ __forceinline__ void bulk_commit() { asm volatile("cp.async.bulk.commit_group;" ::: "memory"); }
__device__ __forceinline__ void fence_async_smem() { asm volatile("fence.proxy.async.shared::cta;" ::: "memory"); }
__device__ __forceinline__ void wg_fence() { asm volatile("wgmma.fence.sync.aligned;" ::: "memory"); }
__device__ __forceinline__ void wg_commit() { asm volatile("wgmma.commit_group.sync.aligned;" ::: "memory"); }
template <int N> __device__ __forceinline__ void wg_wait() { asm volatile("wgmma.wait_group.sync.aligned %0;" :: "n"(N) : "memory"); }

constexpr uint32_t HI_SW = (1u << 30) | 64u, HI_H = 16u;
__host__ __device__ constexpr uint32_t desc_lo(uint32_t addr, uint32_t lbo) { return (addr >> 4) | ((lbo >> 4) << 16); }

#define R8(a, o) "+f"(a[o + 0]), "+f"(a[o + 1]), "+f"(a[o + 2]), "+f"(a[o + 3]), "+f"(a[o + 4]), "+f"(a[o + 5]), "+f"(a[o + 6]), "+f"(a[o + 7])
#define R32(a, o) R8(a, o), R8(a, o + 8), R8(a, o + 16), R8(a, o + 24)

template <uint32_t HA, int O = 0, int N>
__device__ __forceinline__ void wgmma_n256(float (&d)[N], uint32_t da, uint32_t db, int scale_d) {
    asm volatile("{\n.reg .pred p;\n.reg .b64 da, db;\nsetp.ne.b32 p, %130, 0;\nmov.b64 da, {%128, %131};\nmov.b64 db, {%129, %132};\n"
        "wgmma.mma_async.sync.aligned.m64n256k16.f32.bf16.bf16 "
        "{%0,%1,%2,%3,%4,%5,%6,%7,%8,%9,%10,%11,%12,%13,%14,%15,%16,%17,%18,%19,%20,%21,%22,%23,%24,%25,%26,%27,%28,%29,%30,%31,"
        "%32,%33,%34,%35,%36,%37,%38,%39,%40,%41,%42,%43,%44,%45,%46,%47,%48,%49,%50,%51,%52,%53,%54,%55,%56,%57,%58,%59,%60,%61,%62,%63,"
        "%64,%65,%66,%67,%68,%69,%70,%71,%72,%73,%74,%75,%76,%77,%78,%79,%80,%81,%82,%83,%84,%85,%86,%87,%88,%89,%90,%91,%92,%93,%94,%95,"
        "%96,%97,%98,%99,%100,%101,%102,%103,%104,%105,%106,%107,%108,%109,%110,%111,%112,%113,%114,%115,%116,%117,%118,%119,%120,%121,%122,%123,%124,%125,%126,%127},"
        " da, db, p, 1, 1, 0, 1;\n}\n"
        : R32(d, O + 0), R32(d, O + 32), R32(d, O + 64), R32(d, O + 96)
        : "r"(da), "r"(db), "r"(scale_d), "n"(HA), "n"(HI_SW));
}
template <uint32_t HA, int O = 0, int N>
__device__ __forceinline__ void wgmma_n176(float (&d)[N], uint32_t da, uint32_t db, int scale_d) {
    asm volatile("{\n.reg .pred p;\n.reg .b64 da, db;\nsetp.ne.b32 p, %90, 0;\nmov.b64 da, {%88, %91};\nmov.b64 db, {%89, %92};\n"
        "wgmma.mma_async.sync.aligned.m64n176k16.f32.bf16.bf16 "
        "{%0,%1,%2,%3,%4,%5,%6,%7,%8,%9,%10,%11,%12,%13,%14,%15,%16,%17,%18,%19,%20,%21,%22,%23,%24,%25,%26,%27,%28,%29,%30,%31,"
        "%32,%33,%34,%35,%36,%37,%38,%39,%40,%41,%42,%43,%44,%45,%46,%47,%48,%49,%50,%51,%52,%53,%54,%55,%56,%57,%58,%59,%60,%61,%62,%63,"
        "%64,%65,%66,%67,%68,%69,%70,%71,%72,%73,%74,%75,%76,%77,%78,%79,%80,%81,%82,%83,%84,%85,%86,%87},"
        " da, db, p, 1, 1, 0, 1;\n}\n"
        : R32(d, O + 0), R32(d, O + 32), R8(d, O + 64), R8(d, O + 72), R8(d, O + 80)
        : "r"(da), "r"(db), "r"(scale_d), "n"(HA), "n"(HI_SW));
}
template <uint32_t HA, int O = 0, int N>
__device__ __forceinline__ void wgmma_n128(float (&d)[N], uint32_t da, uint32_t db, int scale_d) {
    asm volatile("{\n.reg .pred p;\n.reg .b64 da, db;\nsetp.ne.b32 p, %66, 0;\nmov.b64 da, {%64, %67};\nmov.b64 db, {%65, %68};\n"
        "wgmma.mma_async.sync.aligned.m64n128k16.f32.bf16.bf16 "
        "{%0,%1,%2,%3,%4,%5,%6,%7,%8,%9,%10,%11,%12,%13,%14,%15,%16,%17,%18,%19,%20,%21,%22,%23,%24,%25,%26,%27,%28,%29,%30,%31,"
        "%32,%33,%34,%35,%36,%37,%38,%39,%40,%41,%42,%43,%44,%45,%46,%47,%48,%49,%50,%51,%52,%53,%54,%55,%56,%57,%58,%59,%60,%61,%62,%63},"
        " da, db, p, 1, 1, 0, 1;\n}\n"
        : R32(d, O + 0), R32(d, O + 32)
        : "r"(da), "r"(db), "r"(scale_d), "n"(HA), "n"(HI_SW));
}
__device__ __forceinline__ void wgmma_n64_rs(float (&d)[32], const uint32_t* a, uint32_t db, int scale_d) {
    asm volatile("{\n.reg .pred p;\n.reg .b64 db;\nsetp.ne.b32 p, %37, 0;\nmov.b64 db, {%36, %38};\n"
        "wgmma.mma_async.sync.aligned.m64n64k16.f32.bf16.bf16 "
        "{%0,%1,%2,%3,%4,%5,%6,%7,%8,%9,%10,%11,%12,%13,%14,%15,%16,%17,%18,%19,%20,%21,%22,%23,%24,%25,%26,%27,%28,%29,%30,%31},"
        " {%32,%33,%34,%35}, db, p, 1, 1, 1;\n}\n"
        : R32(d, 0)
        : "r"(a[0]), "r"(a[1]), "r"(a[2]), "r"(a[3]), "r"(db), "r"(scale_d), "n"(HI_SW));
}
template <int M, int N> __device__ __forceinline__ void fence_regs(float (&d)[N]) {
#pragma unroll
    for (int i = 0; i < M; i++) asm volatile("" : "+f"(d[i]) :: "memory");
}

__device__ __forceinline__ uint32_t pack_bf16(float lo, float hi) {
    uint32_t r;
    asm("cvt.rn.bf16x2.f32 %0, %1, %2;" : "=r"(r) : "f"(hi), "f"(lo));
    return r;
}
__device__ __forceinline__ float gelu_gate(float g) {
    const float K0 = -2.3022081986f;
    const float K1 = -0.1029432397f;
    float t = g * fmaf(g * g, K1, K0);
    float e, r;
    asm("ex2.approx.ftz.f32 %0, %1;" : "=f"(e) : "f"(t));
    asm("rcp.approx.ftz.f32 %0, %1;" : "=f"(r) : "f"(1.0f + e));
    return r;
}
__device__ __forceinline__ float geglu(float g, float u) { return (g * u) * gelu_gate(g); }
__device__ __forceinline__ uint32_t gelu2(float lo, float hi) { return pack_bf16(lo * gelu_gate(lo), hi * gelu_gate(hi)); }
__device__ __forceinline__ uint32_t mul_bf16x2(uint32_t a, uint32_t b) {
    uint32_t r;
    asm("mul.rn.bf16x2 %0, %1, %2;" : "=r"(r) : "r"(a), "r"(b));
    return r;
}
__device__ __forceinline__ uint32_t geglu2(uint32_t g, uint32_t u) {
    float lo = geglu(__uint_as_float(g << 16), __uint_as_float(u << 16));
    float hi = geglu(__uint_as_float(g & 0xffff0000u), __uint_as_float(u & 0xffff0000u));
    return pack_bf16(lo, hi);
}
__device__ __forceinline__ void stsm_x4(uint32_t addr, uint32_t r0, uint32_t r1, uint32_t r2, uint32_t r3) {
    asm volatile("stmatrix.sync.aligned.m8n8.x4.shared.b16 [%0], {%1, %2, %3, %4};"
                 :: "r"(addr), "r"(r0), "r"(r1), "r"(r2), "r"(r3) : "memory");
}

constexpr int TN = 5, TR = 4, RB = 9;
struct Maps { CUtensorMap x64, g16, gp16, w64[2], part[2], x128, d, out; };
struct Ptrs { const uint8_t *wg, *wu, *wd; uint8_t* o; };

struct Consumer {
    uint32_t st_h;
    int lane, wg;

    __device__ __forceinline__ void release(int bar_idx) const {
        if (lane == 0) mbar_arrive(bars + 8 * bar_idx);
    }
    __device__ __forceinline__ void wait_full(int bar_idx, uint32_t parity) const { mbar_wait(bars + 8 * bar_idx, parity); }
    __device__ __forceinline__ void stage(int c, uint32_t parity, uint32_t r0, uint32_t r1, uint32_t r2, uint32_t r3) const {
        if ((c & 3) == 0) mbar_wait(bars + 8 * (BAR_SEMPTY + 2 * wg + (c >> 2)), parity);
        stsm_x4(st_h + c * 2048, r0, r1, r2, r3);
    }
    __device__ __forceinline__ void publish(int block) const {
        fence_async_smem();
        __syncwarp();
        release(BAR_SFULL + 2 * wg + block);
    }
    __device__ __forceinline__ void stage_geglu(int c, uint32_t parity, const uint32_t (&pk)[64]) const {
        const int q = 4 * c;
        stage(c, parity, geglu2(pk[q], pk[32 + q]), geglu2(pk[q + 1], pk[33 + q]), geglu2(pk[q + 2], pk[34 + q]), geglu2(pk[q + 3], pk[35 + q]));
        if ((c & 3) == 3) publish(c >> 2);
    }
    __device__ __forceinline__ void mma_a(float (&acc)[128], int s, bool first = false) const {
        const uint32_t da = desc_lo(base, 16) + s * 3072 + wg * 512, db = desc_lo(base + 16384, 8192) + s * 3072;
        wg_fence();
        wgmma_n256<HI_SW>(acc, da, db, first ? 0 : 1);
        wgmma_n256<HI_SW>(acc, da + 2, db + 128, 1);
        wgmma_n256<HI_SW>(acc, da + 4, db + 256, 1);
        wgmma_n256<HI_SW>(acc, da + 6, db + 384, 1);
        wg_commit();
    }
    __device__ __forceinline__ void mma_c(float (&acc)[88], int s, int up, bool first = false) const {
        const uint32_t da = desc_lo(base + 49152, 16) + s * 4096 + wg * 512, db = desc_lo(base, 8192) + up * 1536 + s * 4096;
        wg_fence();
        wgmma_n176<HI_SW>(acc, da, db, first ? 0 : 1);
        wgmma_n176<HI_SW>(acc, da + 2, db + 128, 1);
        wgmma_n176<HI_SW>(acc, da + 4, db + 256, 1);
        wgmma_n176<HI_SW>(acc, da + 6, db + 384, 1);
        wg_commit();
    }
    __device__ __forceinline__ void mma_b(float (&acc)[64], int s, bool first = false) const {
        const uint32_t da = desc_lo(base + 16384, 128) + s * 2048 + wg * 128, db = desc_lo(base, 8192) + s * 2048;
        wg_fence();
        wgmma_n128<HI_H>(acc, da, db, first ? 0 : 1);
        wgmma_n128<HI_H>(acc, da + 256, db + 128, 1);
        wgmma_n128<HI_H>(acc, da + 512, db + 256, 1);
        wgmma_n128<HI_H>(acc, da + 768, db + 384, 1);
        wg_commit();
    }
    __device__ __forceinline__ void step_a(float (&acc)[128], int kb) const {
        mma_a(acc, kb & 3);
        release(BAR_EMPTY_A + ((kb - 1) & 3));
    }
    __device__ __forceinline__ void next_a(int kb) const { wait_full(BAR_FULL_A + ((kb + 1) & 3), ((kb + 1) >> 2) & 1); }
};

__global__ void __launch_bounds__(NUM_THREADS, 1) geglu_ffn_kernel(const Ptrs pp, const __grid_constant__ Maps mp) {
    extern __shared__ __align__(1024) uint8_t smem_raw[];
    const int warp = __shfl_sync(0xffffffffu, threadIdx.x >> 5, 0);
    const int lane = threadIdx.x & 31;

    uint32_t sm;
    asm("mov.u32 %0, %%smid;" : "=r"(sm));
    const int tpc = sm >> 1;
    const int q7 = ((tpc - 32) * 37) >> 8;
    const bool extra = (tpc >> 1) == 30;
    const int grp = tpc < 32 ? tpc & 7 : tpc < 60 ? tpc - 31 - 7 * q7 : 0;
    const int j_blk = tpc < 32 ? tpc >> 3 : tpc < 60 ? 4 + q7 : tpc - 58;
    const int m_blk = extra ? (sm & 3) * 4 : grp * 2 + (sm & 1);
    const int col0 = extra ? 54 : j_blk * 2;

    const uint32_t full_c = bars + 8 * BAR_FULL_C, piece = bars + 8 * BAR_PIECE;
    if (warp == 8) {
        if (!extra && elect_one()) {
            const uint32_t b = base + 2 * 65536;
            mbar_init(piece, 1);
            mbar_init(piece + 8, 1);
            mbar_init(piece + 16, 1);
            mbar_init(full_c + 32, 1);
            mbar_init(full_c + 40, 1);
            asm volatile("fence.mbarrier_init.release.cluster;" ::: "memory");
            mbar_expect_tx(piece, 8192 + 6144);
            tma_2d(b + 49152, &mp.x64, piece, 0, m_blk * 128);
            tma_3d(b, &mp.g16, piece, 0, 0, col0);
            tma_3d(b + 4096, &mp.gp16, piece, 0, 0, j_blk);
            mbar_expect_tx(piece + 8, 8192);
            tma_2d(b + 57344, &mp.x64, piece + 8, 0, m_blk * 128 + 64);
            mbar_expect_tx(piece + 16, 6144);
            tma_3d(b + 6144, &mp.g16, piece + 16, 0, 16, col0);
            tma_3d(b + 10240, &mp.gp16, piece + 16, 0, 16, j_blk);
            mbar_expect_tx(full_c + 32, 12288);
            tma_3d(b + 12288, &mp.g16, full_c + 32, 0, 32, col0);
            tma_3d(b + 16384, &mp.gp16, full_c + 32, 0, 32, j_blk);
            tma_3d(b + 18432, &mp.g16, full_c + 32, 0, 48, col0);
            tma_3d(b + 22528, &mp.gp16, full_c + 32, 0, 48, j_blk);
            mbar_expect_tx(full_c + 40, 24576);
            tma_3d(b + 24576, &mp.w64[1], full_c + 40, 0, 0, col0);
            tma_3d(b + 40960, &mp.part[1], full_c + 40, 0, 0, j_blk);
#pragma unroll
            for (int i = 0; i < 4; i++) mbar_init(full_c + 8 * i, 1);
#pragma unroll
            for (int i = 0; i < 6; i++) mbar_init(bars + 8 * (BAR_EMPTY_C + i), 8);
            asm volatile("fence.mbarrier_init.release.cluster;" ::: "memory");
        }
        __syncwarp();
        asm volatile("bar.arrive 4, 384;" ::: "memory");
    } else {
        asm volatile("bar.sync 4, %0;" :: "r"(384) : "memory");
        asm volatile("nanosleep.u32 0;" ::: "memory");
    }

    if (warp < 8) {
        if (warp == 0) {
            if (elect_one()) {
#pragma unroll
                for (int i = 0; i < BAR_FULL_C; i++) {
                    const bool empty = (i >= BAR_EMPTY_A && i < BAR_FULL_B) || (i >= BAR_EMPTY_B && i < BAR_SFULL);
                    mbar_init(bars + 8 * i, empty ? 8 : (i >= BAR_SFULL && i < BAR_SEMPTY) ? 4 : 1);
                }
                asm volatile("fence.mbarrier_init.release.cluster;" ::: "memory");
            }
            __syncwarp();
            asm volatile("bar.arrive 2, %0;" :: "r"(extra ? 160 : 128) : "memory");
        }
        asm volatile("setmaxnreg.inc.sync.aligned.u32 240;");
        asm volatile("bar.sync 1, 256;" ::: "memory");
        Consumer c;
        c.lane = lane;
        c.wg = warp >> 2;
        c.st_h = base + STAGING_OFF + c.wg * 16384 + (warp & 3) * 512 + (lane & 8) * 32 + (lane >> 4) * 128 + (lane & 7) * 16;
        const bool always = sm != 0xffffffffu;

        uint32_t pk[64], gp[12], up[12];
        if (extra) {
#pragma unroll
            for (int i = 4; i < 12; i++) asm volatile("" : "=r"(gp[i]), "=r"(up[i]));
#pragma unroll
            for (int i = 0; i < 64; i++) asm volatile("" : "=r"(pk[i]));
            c.wait_full(BAR_FULL_A, 0);
        } else {
            float accg[88], accu[88];
#pragma unroll
            for (int i = 0; i < 88; i++) asm volatile("" : "=f"(accg[i]), "=f"(accu[i]));
            const uint32_t da = desc_lo(base + 2 * 65536 + 49152, 16) + c.wg * 512;
            constexpr uint32_t dq = desc_lo(base + 2 * 65536, 2048);
            c.wait_full(BAR_PIECE + c.wg, 0);
            c.wait_full(BAR_PIECE, 0);
            wg_fence();
            wgmma_n176<HI_SW>(accg, da, dq, 0);
            c.wait_full(BAR_PIECE + 2, 0);
            wg_fence();
            wgmma_n176<HI_SW>(accg, da + 2, dq + 384, 1);
            c.wait_full(BAR_FULL_C + 4, 0);
            wg_fence();
            wgmma_n176<HI_SW>(accg, da + 4, dq + 768, 1);
            wgmma_n176<HI_SW>(accg, da + 6, dq + 1152, 1);
            wg_commit();
            c.wait_full(BAR_FULL_C + 5, 0);
            if (c.wg) asm volatile("bar.sync 6, 256;" ::: "memory");
            c.mma_c(accu, 2, 1, true);
            if (!c.wg) asm volatile("bar.arrive 6, 256;" ::: "memory");
            wg_wait<1>();
            c.release(BAR_EMPTY_C + 4);
            c.wait_full(BAR_FULL_C, 0);
            int s = 0, ps = 2;
            uint32_t ph = 0;
#pragma unroll 1
            for (int kb = 1; kb < 15; kb++) {
                wg_wait<0>();
                c.mma_c(accg, s, 0);
                c.release(BAR_EMPTY_C + 2 * ps + 1);
                c.wait_full(BAR_FULL_C + 2 * s + 1, ph);
                wg_wait<0>();
                c.mma_c(accu, s, 1);
                c.release(BAR_EMPTY_C + 2 * s);
                ps = s;
                if (++s == 3) s = 0;
                if (s == 2) ph ^= 1;
                c.wait_full(BAR_FULL_C + 2 * s, ph);
            }
            wg_wait<0>();
            c.mma_c(accg, 2, 0);
            c.release(BAR_EMPTY_C + 3);
            c.wait_full(BAR_FULL_C + 5, 1);
            c.mma_c(accu, 2, 1);
            wg_wait<1>();
            fence_regs<88>(accg);
            c.release(BAR_EMPTY_C + 4);
#pragma unroll
            for (int i = 0; i < 32; i++) asm volatile("" : "=r"(pk[i]));
#pragma unroll
            for (int i = 0; i < 12; i++) asm volatile("" : "=r"(gp[i]));
            if (always) {
#pragma unroll
                for (int i = 0; i < 12; i++) {
                    gp[i] = i < 4 ? gelu2(accg[64 + 2 * i], accg[65 + 2 * i]) : pack_bf16(accg[64 + 2 * i], accg[65 + 2 * i]);
                    asm volatile("" : "+r"(gp[i]));
                }
#pragma unroll
                for (int i = 0; i < 32; i++) {
                    pk[i] = pack_bf16(accg[2 * i], accg[2 * i + 1]);
                    asm volatile("" : "+r"(pk[i]));
                }
            }
            c.wait_full(BAR_FULL_A, 0);
            wg_wait<0>();
            fence_regs<88>(accu);
            c.release(BAR_EMPTY_C + 5);
#pragma unroll
            for (int i = 0; i < 12; i++) up[i] = pack_bf16(accu[64 + 2 * i], accu[65 + 2 * i]);
            stsm_x4(c.st_h + 8192, mul_bf16x2(gp[0], up[0]), mul_bf16x2(gp[1], up[1]), mul_bf16x2(gp[2], up[2]), mul_bf16x2(gp[3], up[3]));
#pragma unroll
            for (int i = 0; i < 32; i++) pk[32 + i] = pack_bf16(accu[2 * i], accu[2 * i + 1]);
        }

        float acc[128];
#pragma unroll
        for (int i = 0; i < 128; i++) asm volatile("" : "=f"(acc[i]));
        auto stage_part = [&](int i) {
            stsm_x4(c.st_h + 8192 + i * 512, geglu2(gp[i], up[i]), geglu2(gp[i + 1], up[i + 1]), geglu2(gp[i + 2], up[i + 2]), geglu2(gp[i + 3], up[i + 3]));
        };
        c.mma_a(acc, 0, true);
        c.wait_full(BAR_FULL_A + 1, 0);
        c.mma_a(acc, 1);
        if (!extra) stage_part(4);
        wg_wait<1>();
        c.release(BAR_EMPTY_A);
        if (!extra) {
            stage_part(8);
            c.publish(1);
        }
        c.wait_full(BAR_FULL_A + 2, 0);
#pragma unroll 1
        for (int t = extra ? 0 : 2;; t++) {
#pragma unroll
            for (int kb = 2; kb < 10; kb++) {
                wg_wait<0>();
                c.step_a(acc, kb);
                if (t > 0) c.stage_geglu(kb - 2, t & 1, pk);
                c.next_a(kb);
            }
#pragma unroll 1
            for (int kb = 10; kb < 15; kb++) {
                wg_wait<0>();
                c.step_a(acc, kb);
                c.next_a(kb);
            }
            if (t == 3) break;
            c.mma_a(acc, 3);
            wg_wait<1>();
            c.release(BAR_EMPTY_A + 2);
            c.wait_full(BAR_FULL_A, 0);
            wg_wait<0>();
            fence_regs<128>(acc);
            c.release(BAR_EMPTY_A + 3);
#pragma unroll
            for (int i = 0; i < 64; i++) pk[i] = pack_bf16(acc[2 * i], acc[2 * i + 1]);
            c.mma_a(acc, 0, true);
            c.wait_full(BAR_FULL_A + 1, 0);
            c.mma_a(acc, 1);
            wg_wait<1>();
            c.release(BAR_EMPTY_A);
            c.wait_full(BAR_FULL_A + 2, 0);
        }
        wg_wait<0>();
        c.step_a(acc, 15);
        auto stage_acc = [&](int q) {
            const int g = 8 * q, u = 64 + 8 * q;
            c.stage(q, 0, pack_bf16(geglu(acc[g], acc[u]), geglu(acc[g + 1], acc[u + 1])), pack_bf16(geglu(acc[g + 2], acc[u + 2]), geglu(acc[g + 3], acc[u + 3])),
                    pack_bf16(geglu(acc[g + 4], acc[u + 4]), geglu(acc[g + 5], acc[u + 5])), pack_bf16(geglu(acc[g + 6], acc[u + 6]), geglu(acc[g + 7], acc[u + 7])));
        };
        if (extra) {
            wg_wait<0>();
            fence_regs<128>(acc);
#pragma unroll
            for (int q = 0; q < 8; q++) {
                stage_acc(q);
                if ((q & 3) == 3) c.publish(q >> 2);
            }
            return;
        }
        c.wait_full(BAR_FULL_B, 0);

        constexpr int KB0 = 17;
        float acc4[64];
        uint32_t h0, h1;
#pragma unroll
        for (int kb = 0; kb < KB0; kb++) {
            wg_wait<0>();
            if (kb == 0) fence_regs<128>(acc);
            c.mma_b(acc4, kb % STB, kb == 0);
            c.release(kb == 0 ? BAR_EMPTY_A + 3 : BAR_EMPTY_B + (kb - 1) % STB);
            if (!(kb & 1)) asm volatile("" : "=r"(h0), "=r"(h1));
            if (always) {
                if (kb % 8 == 0 && kb) c.publish(kb / 8 - 1);
                if (kb < 16) {
                    const int g = 4 * kb, u = 64 + g;
                    const uint32_t r0 = pack_bf16(geglu(acc[g], acc[u]), geglu(acc[g + 1], acc[u + 1]));
                    const uint32_t r1 = pack_bf16(geglu(acc[g + 2], acc[u + 2]), geglu(acc[g + 3], acc[u + 3]));
                    if (kb & 1) {
                        c.stage(kb >> 1, 0, h0, h1, r0, r1);
                    } else {
                        h0 = r0;
                        h1 = r1;
                        asm volatile("" : "+r"(h0), "+r"(h1));
                    }
                }
            }
            c.wait_full(BAR_FULL_B + (kb + 1) % STB, ((kb + 1) / STB) & 1);
        }
        int s = KB0 % STB, ps = (KB0 - 1) % STB;
        uint32_t ph = (KB0 / STB) & 1;
#pragma unroll 1
        for (int kb = KB0; kb < KB_FF - TN; kb++) {
            wg_wait<0>();
            c.mma_b(acc4, s);
            c.release(BAR_EMPTY_B + ps);
            ps = s;
            if (++s == STB) { s = 0; ph ^= 1; }
            c.wait_full(BAR_FULL_B + s, ph);
        }
        c.wait_full(BAR_SEMPTY + 2 * c.wg, 1);
        c.wait_full(BAR_SEMPTY + 2 * c.wg + 1, 1);
        const uint32_t strip = base + STAGING_OFF + c.wg * 16384 + (warp & 3) * 2048;
        const uint32_t st_row = strip + (lane & 15) * 128, st_sw = ((lane >> 4) ^ (lane & 7)) << 4;
        const int row0 = m_blk * 128 + warp * 16;
        const uint32_t ld_row = strip + (lane >> 3) * 128 + (((lane & 7) ^ (lane >> 3)) << 4);
        uint8_t* optr = pp.o + (size_t)(row0 + (lane >> 3)) * 2048 + j_blk * 256 + (lane & 7) * 16;
        auto stage_out = [&](int h) {
#pragma unroll
            for (int q = 0; q < 4; q++) {
                const int i = 32 * h + 8 * q;
                stsm_x4(st_row + h * 8192 + (st_sw ^ (q << 5)), pack_bf16(acc4[i], acc4[i + 1]), pack_bf16(acc4[i + 2], acc4[i + 3]),
                        pack_bf16(acc4[i + 4], acc4[i + 5]), pack_bf16(acc4[i + 6], acc4[i + 7]));
            }
        };
        wg_wait<0>();
        if (!c.wg) {
#pragma unroll
            for (int kb = KB_FF - TN; kb < KB_FF; kb++) {
                if (kb > KB_FF - TN) c.wait_full(BAR_FULL_B + kb % STB, (kb / STB) & 1);
                c.mma_b(acc4, kb % STB);
            }
            asm volatile("bar.arrive 6, 256;" ::: "memory");
            wg_wait<0>();
            fence_regs<64>(acc4);
#pragma unroll
            for (int h = 0; h < 2; h++) {
                stage_out(h);
                fence_async_smem();
                __syncwarp();
                if (elect_one()) {
                    tma_store_2d(&mp.out, strip + h * 8192, j_blk * 128 + h * 64, row0);
                    bulk_commit();
                }
            }
            if (elect_one()) asm volatile("cp.async.bulk.wait_group.read 0;" ::: "memory");
            __syncwarp();
        } else {
            float half[2][32];
            uint32_t af[16 * TR];
            const uint32_t ld_h = c.st_h - STAGING_OFF + 2048;
#pragma unroll
            for (int kb = KB_FF - TN + 1; kb < KB_FF; kb++) {
                c.wait_full(BAR_FULL_B + kb % STB, (kb / STB) & 1);
#pragma unroll
                for (int q = 4 * (kb - KB_FF + TR); q >= 0 && q < 4 * (kb + 1 - KB_FF + TR); q++)
                    asm volatile("ldmatrix.sync.aligned.m8n8.x4.shared.b16 {%0, %1, %2, %3}, [%4];"
                                 : "=r"(af[4 * q]), "=r"(af[4 * q + 1]), "=r"(af[4 * q + 2]), "=r"(af[4 * q + 3])
                                 : "r"(ld_h + (kb % STB) * 32768 + (q & 3) * 4096) : "memory");
            }
            auto mma_half = [&](int h, int q0, int q1) {
                wg_fence();
#pragma unroll
                for (int q = q0; q < q1; q++)
                    wgmma_n64_rs(half[h], af + 4 * q, desc_lo(base, 8192) + ((KB_FF - TR + (q >> 2)) % STB) * 2048 + h * 512 + (q & 3) * 128, q);
                wg_commit();
            };
            auto add_half = [&](int h) {
                fence_regs<32>(half[h]);
#pragma unroll
                for (int i = 0; i < 32; i++) acc4[32 * h + i] += half[h][i];
            };
            auto store_out = [&](int h) {
                __syncwarp();
                uint4 v[4];
#pragma unroll
                for (int i = 0; i < 4; i++)
                    asm volatile("ld.shared.v4.u32 {%0, %1, %2, %3}, [%4];" : "=r"(v[i].x), "=r"(v[i].y), "=r"(v[i].z), "=r"(v[i].w)
                                 : "r"((ld_row ^ ((i & 1) << 6)) + i * 512 + h * 8192) : "memory");
#pragma unroll
                for (int i = 0; i < 4; i++)
                    asm volatile("st.global.v4.u32 [%0], {%1, %2, %3, %4};" :: "l"(optr + i * 8192 + h * 128), "r"(v[i].x), "r"(v[i].y), "r"(v[i].z), "r"(v[i].w) : "memory");
            };
            asm volatile("bar.sync 6, 256;" ::: "memory");
#pragma unroll
            for (int kb = KB_FF - TN; kb < KB_FF - TR; kb++) c.mma_b(acc4, kb % STB);
            mma_half(0, 0, 4 * TR);
            mma_half(1, 0, RB);
            wg_wait<1>();
            fence_regs<64>(acc4);
            add_half(0);
            stage_out(0);
            mma_half(1, RB, 4 * TR);
            store_out(0);
            wg_wait<0>();
            add_half(1);
            stage_out(1);
            store_out(1);
        }
    } else {
        asm volatile("setmaxnreg.dec.sync.aligned.u32 24;");
        if (warp != 8) {
            asm volatile("bar.sync 2, %0;" :: "r"(extra ? 160 : 128) : "memory");
            uint32_t cnt;
            if (warp == 11) asm volatile("ld.relaxed.gpu.global.u32 %0, [%1];" : "=r"(cnt) : "l"(g_ready + m_blk * 4) : "memory");
            asm volatile("bar.sync 5, 96;" ::: "memory");
            if (elect_one()) {
                if (warp <= 10) {
                    const int w = warp - 9;
                    if (!extra) mbar_arrive(bars + 8 * (BAR_SEMPTY + 2 * w));
#pragma unroll 1
                    for (int b = extra ? 0 : 1; b < 8; b++) {
                        const int t = b >> 1;
                        const bool part = !extra && b == 1;
                        const int m = extra ? m_blk + t : m_blk;
                        const int chunk = part ? 64 + 3 * j_blk : (col0 + (b & 1) + (extra || t == 1 ? 0 : 16 * t - 10)) * 4;
                        uint8_t* dst = g_h + ((size_t)m * (KB_FF * 4) + chunk) * 4096 + w * 2048;
                        const uint32_t src = base + STAGING_OFF + w * 16384 + (b & 1) * 8192;
                        const uint32_t pace = t < 3 ? 300 : 0;
                        mbar_wait_p(bars + 8 * (BAR_SFULL + 2 * w + (b & 1)), (extra ? t : t + b + 1) & 1);
#pragma unroll 1
                        for (int q = 0; q < (part ? 3 : 4); q++) {
                            if (q | (b & 1)) __nanosleep(pace);
                            bulk_store(dst + q * 4096, src + q * 2048, 2048);
                            bulk_commit();
                            asm volatile("cp.async.bulk.wait_group.read 0;" ::: "memory");
                        }
                        mbar_arrive(bars + 8 * (BAR_SEMPTY + 2 * w + (b & 1)));
                        if ((b & 1) && !part) {
                            asm volatile("cp.async.bulk.wait_group 0;" ::: "memory");
                            asm volatile("fence.proxy.async.global;" ::: "memory");
                            asm volatile("red.release.gpu.global.add.u32 [%0], %1;"
                                         :: "l"(g_ready + m * 4 + (extra ? 3 : t - 1)), "r"(extra ? 16 : 2) : "memory");
                        }
                    }
                } else {
                    uint32_t nsm;
                    asm("mov.u32 %0, %%nsmid;" : "=r"(nsm));
                    if (smem_u32(smem_raw) != base || nsm != NUM_CTAS) __trap();
                    prefetch_map(&mp.d);
                    prefetch_map(&mp.out);
                    if (extra) return;
                    const int row = m_blk * 64 + j_blk * 8;
#pragma unroll 1
                    for (int t = 0; t < 2; t++) {
                        mbar_wait_p(bars + 8 * (BAR_PF + t), 0);
#pragma unroll 1
                        for (int r = row; r < row + 8; r++) {
                            prefetch_l2(pp.wg + r * (D_FF * 2) + 2816 + t * 2048, 2048);
                            prefetch_l2(pp.wu + r * (D_FF * 2) + 2816 + t * 2048, 2048);
                        }
                    }
                    mbar_wait_p(bars + 8 * (BAR_PF + 2), 0);
                    prefetch_l2(pp.wd + row * 2048, 16384);
#pragma unroll 1
                    for (int round = 0; round < 4; round++) {
                        uint32_t v, it = 0;
                        while (true) {
                            asm volatile("ld.acquire.gpu.global.u32 %0, [%1];" : "=r"(v) : "l"(g_ready + m_blk * 4 + round) : "memory");
                            if (v - (cnt & ~31u) >= 32u) break;
                            if (++it > (1u << 20)) __trap();
                            __nanosleep(200);
                        }
                        asm volatile("fence.proxy.async.global;" ::: "memory");
                        mbar_arrive(bars + 8 * (BAR_HREADY + round));
                    }
                }
            }
            return;
        }
        if (extra) asm volatile("bar.sync 2, 160;" ::: "memory");
        if (!elect_one()) return;
        if (extra) __nanosleep(2000);
        if (!extra) {
            int s = 0;
            uint32_t ph = 1;
#pragma unroll 1
            for (int i = 2; i < 32; i++) {
                const uint32_t full = full_c + 8 * s, b = base + (s >> 1) * 65536, bw = b + (i & 1) * 24576;
                if (s == 4) ph ^= 1;
                mbar_wait_p(bars + 8 * (BAR_EMPTY_C + s), ph);
                if (i & 1) tma_2d(b + 49152, &mp.x128, full - 8, (i >> 1) * 64, m_blk * 128);
                mbar_expect_tx(full, (i & 1) ? 24576 : 40960);
                tma_3d(bw, &mp.w64[i & 1], full, 0, (i >> 1) * 64, col0);
                tma_3d(bw + 16384, &mp.part[i & 1], full, 0, (i >> 1) * 64, j_blk);
                if (i == 8 + ((3 * m_blk) >> 1)) mbar_arrive(bars + 8 * BAR_PF);
                if (++s == 6) s = 0;
            }
        }
#pragma unroll 1
        for (int i = 0; i < (extra ? 64 : 32); i++) {
            const int s = i & 3, k0 = (i & 15) * 64, t = i >> 4;
            const int c0 = extra ? col0 : col0 + 16 * t + 22;
            const uint32_t full = bars + 8 * (BAR_FULL_A + s), b = base + s * 49152;
            if (i < 4 && !extra) mbar_wait_p(bars + 8 * (BAR_EMPTY_C + (i ? i + 2 : 1)), i >> 1);
            else mbar_wait_p(bars + 8 * (BAR_EMPTY_A + s), ((i >> 2) & 1) ^ 1);
            mbar_expect_tx(full, 49152);
            tma_2d(b, &mp.x128, full, k0, (extra ? m_blk + t : m_blk) * 128);
            tma_3d(b + 16384, &mp.w64[0], full, 0, k0, c0);
            tma_3d(b + 32768, &mp.w64[1], full, 0, k0, c0);
            if (i == 4 + m_blk) mbar_arrive(bars + 8 * (BAR_PF + 1));
            if (i == 20 + (m_blk >> 1)) mbar_arrive(bars + 8 * (BAR_PF + 2));
        }
        if (extra) return;
        const uint8_t* h_src = g_h + (size_t)m_blk * KB_FF * 16384;
        int s = 0;
        uint32_t ph = 1;
#pragma unroll 1
        for (int i = 0; i < KB_FF; i++) {
            const uint32_t full = bars + 8 * (BAR_FULL_B + s);
            if (i < STB) mbar_wait_p(bars + 8 * (BAR_EMPTY_A + ((2 * i + 1) / 3)), 1);
            else mbar_wait_p(bars + 8 * (BAR_EMPTY_B + s), ph);
            mbar_expect_tx(full, 32768);
            tma_3d(base + s * 32768, &mp.d, full, 0, i * 64, col0);
            if (i == 0 || (i & 15) == 6) mbar_wait_p(bars + 8 * (BAR_HREADY + (i >> 4)), 0);
            bulk_load(base + s * 32768 + 16384, h_src + (size_t)i * 16384, 16384, full);
            if (++s == STB) { s = 0; ph ^= 1; }
        }
    }
}

typedef CUresult (*EncodeFn)(CUtensorMap*, CUtensorMapDataType, cuuint32_t, void*, const cuuint64_t*, const cuuint64_t*,
                             const cuuint32_t*, const cuuint32_t*, CUtensorMapInterleave, CUtensorMapSwizzle,
                             CUtensorMapL2promotion, CUtensorMapFloatOOBfill);

void map_2d(EncodeFn enc, CUtensorMap* m, const void* p, int rows, int cols, int box_rows) {
    cuuint64_t dims[2] = {(cuuint64_t)cols, (cuuint64_t)rows};
    cuuint64_t str[1] = {(cuuint64_t)cols * 2};
    cuuint32_t box[2] = {64, (cuuint32_t)box_rows};
    cuuint32_t es[2] = {1, 1};
    enc(m, CU_TENSOR_MAP_DATA_TYPE_BFLOAT16, 2, const_cast<void*>(p), dims, str, box, es, CU_TENSOR_MAP_INTERLEAVE_NONE,
        CU_TENSOR_MAP_SWIZZLE_128B, CU_TENSOR_MAP_L2_PROMOTION_L2_128B, CU_TENSOR_MAP_FLOAT_OOB_FILL_NONE);
}
void map_w(EncodeFn enc, CUtensorMap* m, const void* p, int K, int N, int rows, int atoms) {
    cuuint64_t dims[3] = {64, (cuuint64_t)K, (cuuint64_t)N / 64};
    cuuint64_t str[2] = {(cuuint64_t)N * 2, 128};
    cuuint32_t box[3] = {64, (cuuint32_t)rows, (cuuint32_t)atoms};
    cuuint32_t es[3] = {1, 1, 1};
    enc(m, CU_TENSOR_MAP_DATA_TYPE_BFLOAT16, 3, const_cast<void*>(p), dims, str, box, es, CU_TENSOR_MAP_INTERLEAVE_NONE,
        CU_TENSOR_MAP_SWIZZLE_128B, CU_TENSOR_MAP_L2_PROMOTION_L2_128B, CU_TENSOR_MAP_FLOAT_OOB_FILL_NONE);
}

void map_part(EncodeFn enc, CUtensorMap* m, const void* p, int rows) {
    cuuint64_t dims[3] = {48, (cuuint64_t)D_MODEL, 8};
    cuuint64_t str[2] = {(cuuint64_t)D_FF * 2, 96};
    cuuint32_t box[3] = {64, (cuuint32_t)rows, 1};
    cuuint32_t es[3] = {1, 1, 1};
    enc(m, CU_TENSOR_MAP_DATA_TYPE_BFLOAT16, 3, (char*)const_cast<void*>(p) + 1024 * 2, dims, str, box, es, CU_TENSOR_MAP_INTERLEAVE_NONE,
        CU_TENSOR_MAP_SWIZZLE_128B, CU_TENSOR_MAP_L2_PROMOTION_L2_128B, CU_TENSOR_MAP_FLOAT_OOB_FILL_NONE);
}

}

extern "C" void kernel_launch(void* const* d_in, const int* in_sizes, int n_in, void* d_out, int out_size) {
    (void)in_sizes; (void)n_in; (void)out_size;
    void* fn = nullptr;
    cudaDriverEntryPointQueryResult st;
    cudaGetDriverEntryPoint("cuTensorMapEncodeTiled", &fn, cudaEnableDefault, &st);
    EncodeFn enc = (EncodeFn)fn;
    Maps mp;
    map_2d(enc, &mp.x64, d_in[0], M_TOK, D_MODEL, 64);
    map_2d(enc, &mp.x128, d_in[0], M_TOK, D_MODEL, 128);
    map_w(enc, &mp.g16, d_in[1], D_MODEL, D_FF, 16, 2);
    map_part(enc, &mp.gp16, d_in[1], 16);
    map_w(enc, &mp.w64[0], d_in[1], D_MODEL, D_FF, 64, 2);
    map_w(enc, &mp.w64[1], d_in[2], D_MODEL, D_FF, 64, 2);
    map_part(enc, &mp.part[0], d_in[1], 64);
    map_part(enc, &mp.part[1], d_in[2], 64);
    map_w(enc, &mp.d, d_in[3], D_FF, D_MODEL, 64, 2);
    map_2d(enc, &mp.out, d_out, M_TOK, D_MODEL, 16);
    const Ptrs pp = {(const uint8_t*)d_in[1], (const uint8_t*)d_in[2], (const uint8_t*)d_in[3], (uint8_t*)d_out};
    cudaFuncSetAttribute(geglu_ffn_kernel, cudaFuncAttributeMaxDynamicSharedMemorySize, SMEM_BYTES);
    geglu_ffn_kernel<<<NUM_CTAS, NUM_THREADS, SMEM_BYTES>>>(pp, mp);
}
```

```cpp
#include <cuda_runtime.h>
#include <cuda_bf16.h>
#include <cuda.h>
#include <stdint.h>

namespace {

constexpr int M_TOK = 2048, D_MODEL = 1024, D_FF = 3584;
constexpr int KB_FF = D_FF / 64;
constexpr int NUM_CTAS = 132;
constexpr int NUM_THREADS = 384;

constexpr int STB = 6;
constexpr int RING_BYTES = 196608;
constexpr int STAGING_OFF = RING_BYTES;
constexpr int BAR_OFF = STAGING_OFF + 32768;
constexpr int SMEM_BYTES = BAR_OFF + 512;
constexpr uint32_t base = 1024, bars = base + BAR_OFF;

constexpr int BAR_FULL_A = 0, BAR_EMPTY_A = 4, BAR_FULL_B = 8, BAR_EMPTY_B = 14, BAR_SFULL = 20, BAR_SEMPTY = 24,
              BAR_HREADY = 28, BAR_PF = 32, BAR_FULL_C = 35, BAR_EMPTY_C = 41, BAR_PIECE = 47, BAR_POLL = 49;

__device__ __align__(1024) uint8_t g_h[(size_t)M_TOK * D_FF * 2];
__device__ __align__(16) unsigned int g_ready[16 * 4];

__device__ __forceinline__ uint32_t smem_u32(const void* p) { return (uint32_t)__cvta_generic_to_shared(p); }
__device__ __forceinline__ bool elect_one() {
    uint32_t p;
    asm volatile("{\n.reg .pred p;\nelect.sync _|p, 0xffffffff;\nselp.u32 %0, 1, 0, p;\n}" : "=r"(p));
    return p != 0;
}
__device__ __forceinline__ void mbar_init(uint32_t bar, uint32_t cnt) {
    asm volatile("mbarrier.init.shared::cta.b64 [%0], %1;" :: "r"(bar), "r"(cnt) : "memory");
}
__device__ __forceinline__ void mbar_expect_tx(uint32_t bar, uint32_t bytes) {
    asm volatile("mbarrier.arrive.expect_tx.shared::cta.b64 _, [%0], %1;" :: "r"(bar), "r"(bytes) : "memory");
}
__device__ __forceinline__ void mbar_arrive(uint32_t bar) {
    asm volatile("mbarrier.arrive.shared::cta.b64 _, [%0];" :: "r"(bar) : "memory");
}
__device__ __forceinline__ bool mbar_try(uint32_t bar, uint32_t parity) {
    uint32_t done;
    asm volatile("{\n.reg .pred p;\nmbarrier.try_wait.parity.shared::cta.b64 p, [%1], %2;\nselp.u32 %0, 1, 0, p;\n}"
                 : "=r"(done) : "r"(bar), "r"(parity) : "memory");
    return done != 0;
}
__device__ __forceinline__ void mbar_wait_p(uint32_t bar, uint32_t parity) {
    uint32_t it = 0;
#pragma unroll 1
    while (!mbar_try(bar, parity)) {
        if (++it > (1u << 20)) __trap();
    }
}
__device__ __forceinline__ void mbar_wait(uint32_t bar, uint32_t parity) {
    if (mbar_try(bar, parity)) return;
    uint32_t it = 0;
#pragma unroll 1
    while (!mbar_try(bar, parity)) {
        if (++it > (1u << 21)) break;
    }
}
__device__ __forceinline__ void tma_2d(uint32_t dst, const CUtensorMap* m, uint32_t bar, int c0, int c1) {
    asm volatile("cp.async.bulk.tensor.2d.shared::cluster.global.mbarrier::complete_tx::bytes [%0], [%1, {%3, %4}], [%2];"
                 :: "r"(dst), "l"((uint64_t)m), "r"(bar), "r"(c0), "r"(c1) : "memory");
}
__device__ __forceinline__ void tma_3d(uint32_t dst, const CUtensorMap* m, uint32_t bar, int c0, int c1, int c2) {
    asm volatile("cp.async.bulk.tensor.3d.shared::cluster.global.mbarrier::complete_tx::bytes [%0], [%1, {%3, %4, %5}], [%2];"
                 :: "r"(dst), "l"((uint64_t)m), "r"(bar), "r"(c0), "r"(c1), "r"(c2) : "memory");
}
__device__ __forceinline__ void bulk_load(uint32_t dst, const void* src, uint32_t bytes, uint32_t bar) {
    asm volatile("cp.async.bulk.shared::cluster.global.mbarrier::complete_tx::bytes [%0], [%1], %2, [%3];"
                 :: "r"(dst), "l"(src), "r"(bytes), "r"(bar) : "memory");
}
__device__ __forceinline__ void bulk_store(void* dst, uint32_t src, uint32_t bytes) {
    asm volatile("cp.async.bulk.global.shared::cta.bulk_group [%0], [%1], %2;" :: "l"(dst), "r"(src), "r"(bytes) : "memory");
}
__device__ __forceinline__ void tma_store_2d(const CUtensorMap* m, uint32_t src, int c0, int c1) {
    asm volatile("cp.async.bulk.tensor.2d.global.shared::cta.bulk_group [%0, {%2, %3}], [%1];"
                 :: "l"((uint64_t)m), "r"(src), "r"(c0), "r"(c1) : "memory");
}
__device__ __forceinline__ void prefetch_map(const CUtensorMap* m) {
    asm volatile("prefetch.tensormap [%0];" :: "l"((uint64_t)m) : "memory");
}
__device__ __forceinline__ void prefetch_l2(const void* p, uint32_t bytes) {
    asm volatile("cp.async.bulk.prefetch.L2.global [%0], %1;" :: "l"(p), "r"(bytes) : "memory");
}
__device__ __forceinline__ void bulk_commit() { asm volatile("cp.async.bulk.commit_group;" ::: "memory"); }
__device__ __forceinline__ void fence_async_smem() { asm volatile("fence.proxy.async.shared::cta;" ::: "memory"); }
__device__ __forceinline__ void wg_fence() { asm volatile("wgmma.fence.sync.aligned;" ::: "memory"); }
__device__ __forceinline__ void wg_commit() { asm volatile("wgmma.commit_group.sync.aligned;" ::: "memory"); }
template <int N> __device__ __forceinline__ void wg_wait() { asm volatile("wgmma.wait_group.sync.aligned %0;" :: "n"(N) : "memory"); }

constexpr uint32_t HI_SW = (1u << 30) | 64u, HI_H = 16u;
__host__ __device__ constexpr uint32_t desc_lo(uint32_t addr, uint32_t lbo) { return (addr >> 4) | ((lbo >> 4) << 16); }

#define R8(a, o) "+f"(a[o + 0]), "+f"(a[o + 1]), "+f"(a[o + 2]), "+f"(a[o + 3]), "+f"(a[o + 4]), "+f"(a[o + 5]), "+f"(a[o + 6]), "+f"(a[o + 7])
#define R32(a, o) R8(a, o), R8(a, o + 8), R8(a, o + 16), R8(a, o + 24)

template <uint32_t HA, int O = 0, int N>
__device__ __forceinline__ void wgmma_n256(float (&d)[N], uint32_t da, uint32_t db, int scale_d) {
    asm volatile("{\n.reg .pred p;\n.reg .b64 da, db;\nsetp.ne.b32 p, %130, 0;\nmov.b64 da, {%128, %131};\nmov.b64 db, {%129, %132};\n"
        "wgmma.mma_async.sync.aligned.m64n256k16.f32.bf16.bf16 "
        "{%0,%1,%2,%3,%4,%5,%6,%7,%8,%9,%10,%11,%12,%13,%14,%15,%16,%17,%18,%19,%20,%21,%22,%23,%24,%25,%26,%27,%28,%29,%30,%31,"
        "%32,%33,%34,%35,%36,%37,%38,%39,%40,%41,%42,%43,%44,%45,%46,%47,%48,%49,%50,%51,%52,%53,%54,%55,%56,%57,%58,%59,%60,%61,%62,%63,"
        "%64,%65,%66,%67,%68,%69,%70,%71,%72,%73,%74,%75,%76,%77,%78,%79,%80,%81,%82,%83,%84,%85,%86,%87,%88,%89,%90,%91,%92,%93,%94,%95,"
        "%96,%97,%98,%99,%100,%101,%102,%103,%104,%105,%106,%107,%108,%109,%110,%111,%112,%113,%114,%115,%116,%117,%118,%119,%120,%121,%122,%123,%124,%125,%126,%127},"
        " da, db, p, 1, 1, 0, 1;\n}\n"
        : R32(d, O + 0), R32(d, O + 32), R32(d, O + 64), R32(d, O + 96)
        : "r"(da), "r"(db), "r"(scale_d), "n"(HA), "n"(HI_SW));
}
template <uint32_t HA, int O = 0, int N>
__device__ __forceinline__ void wgmma_n176(float (&d)[N], uint32_t da, uint32_t db, int scale_d) {
    asm volatile("{\n.reg .pred p;\n.reg .b64 da, db;\nsetp.ne.b32 p, %90, 0;\nmov.b64 da, {%88, %91};\nmov.b64 db, {%89, %92};\n"
        "wgmma.mma_async.sync.aligned.m64n176k16.f32.bf16.bf16 "
        "{%0,%1,%2,%3,%4,%5,%6,%7,%8,%9,%10,%11,%12,%13,%14,%15,%16,%17,%18,%19,%20,%21,%22,%23,%24,%25,%26,%27,%28,%29,%30,%31,"
        "%32,%33,%34,%35,%36,%37,%38,%39,%40,%41,%42,%43,%44,%45,%46,%47,%48,%49,%50,%51,%52,%53,%54,%55,%56,%57,%58,%59,%60,%61,%62,%63,"
        "%64,%65,%66,%67,%68,%69,%70,%71,%72,%73,%74,%75,%76,%77,%78,%79,%80,%81,%82,%83,%84,%85,%86,%87},"
        " da, db, p, 1, 1, 0, 1;\n}\n"
        : R32(d, O + 0), R32(d, O + 32), R8(d, O + 64), R8(d, O + 72), R8(d, O + 80)
        : "r"(da), "r"(db), "r"(scale_d), "n"(HA), "n"(HI_SW));
}
template <uint32_t HA, int O = 0, int N>
__device__ __forceinline__ void wgmma_n128(float (&d)[N], uint32_t da, uint32_t db, int scale_d) {
    asm volatile("{\n.reg .pred p;\n.reg .b64 da, db;\nsetp.ne.b32 p, %66, 0;\nmov.b64 da, {%64, %67};\nmov.b64 db, {%65, %68};\n"
        "wgmma.mma_async.sync.aligned.m64n128k16.f32.bf16.bf16 "
        "{%0,%1,%2,%3,%4,%5,%6,%7,%8,%9,%10,%11,%12,%13,%14,%15,%16,%17,%18,%19,%20,%21,%22,%23,%24,%25,%26,%27,%28,%29,%30,%31,"
        "%32,%33,%34,%35,%36,%37,%38,%39,%40,%41,%42,%43,%44,%45,%46,%47,%48,%49,%50,%51,%52,%53,%54,%55,%56,%57,%58,%59,%60,%61,%62,%63},"
        " da, db, p, 1, 1, 0, 1;\n}\n"
        : R32(d, O + 0), R32(d, O + 32)
        : "r"(da), "r"(db), "r"(scale_d), "n"(HA), "n"(HI_SW));
}
__device__ __forceinline__ void wgmma_n64_rs(float (&d)[32], const uint32_t* a, uint32_t db, int scale_d) {
    asm volatile("{\n.reg .pred p;\n.reg .b64 db;\nsetp.ne.b32 p, %37, 0;\nmov.b64 db, {%36, %38};\n"
        "wgmma.mma_async.sync.aligned.m64n64k16.f32.bf16.bf16 "
        "{%0,%1,%2,%3,%4,%5,%6,%7,%8,%9,%10,%11,%12,%13,%14,%15,%16,%17,%18,%19,%20,%21,%22,%23,%24,%25,%26,%27,%28,%29,%30,%31},"
        " {%32,%33,%34,%35}, db, p, 1, 1, 1;\n}\n"
        : R32(d, 0)
        : "r"(a[0]), "r"(a[1]), "r"(a[2]), "r"(a[3]), "r"(db), "r"(scale_d), "n"(HI_SW));
}
template <int M, int N> __device__ __forceinline__ void fence_regs(float (&d)[N]) {
#pragma unroll
    for (int i = 0; i < M; i++) asm volatile("" : "+f"(d[i]) :: "memory");
}

__device__ __forceinline__ uint32_t pack_bf16(float lo, float hi) {
    uint32_t r;
    asm("cvt.rn.bf16x2.f32 %0, %1, %2;" : "=r"(r) : "f"(hi), "f"(lo));
    return r;
}
__device__ __forceinline__ float gelu_gate(float g) {
    const float K0 = -2.3022081986f;
    const float K1 = -0.1029432397f;
    float t = g * fmaf(g * g, K1, K0);
    float e, r;
    asm("ex2.approx.ftz.f32 %0, %1;" : "=f"(e) : "f"(t));
    asm("rcp.approx.ftz.f32 %0, %1;" : "=f"(r) : "f"(1.0f + e));
    return r;
}
__device__ __forceinline__ float geglu(float g, float u) { return (g * u) * gelu_gate(g); }
__device__ __forceinline__ uint32_t gelu2(float lo, float hi) { return pack_bf16(lo * gelu_gate(lo), hi * gelu_gate(hi)); }
__device__ __forceinline__ uint32_t mul_bf16x2(uint32_t a, uint32_t b) {
    uint32_t r;
    asm("mul.rn.bf16x2 %0, %1, %2;" : "=r"(r) : "r"(a), "r"(b));
    return r;
}
__device__ __forceinline__ uint32_t geglu2(uint32_t g, uint32_t u) {
    float lo = geglu(__uint_as_float(g << 16), __uint_as_float(u << 16));
    float hi = geglu(__uint_as_float(g & 0xffff0000u), __uint_as_float(u & 0xffff0000u));
    return pack_bf16(lo, hi);
}
__device__ __forceinline__ void stsm_x4(uint32_t addr, uint32_t r0, uint32_t r1, uint32_t r2, uint32_t r3) {
    asm volatile("stmatrix.sync.aligned.m8n8.x4.shared.b16 [%0], {%1, %2, %3, %4};"
                 :: "r"(addr), "r"(r0), "r"(r1), "r"(r2), "r"(r3) : "memory");
}

constexpr int TN = 5, TR = 4, RB = 9;
struct Maps { CUtensorMap x64, g16, gp16, w64[2], part[2], x128, d, out; };
struct Ptrs { const uint8_t *wg, *wu, *wd; uint8_t* o; };

struct Consumer {
    uint32_t st_h;
    int lane, wg;

    __device__ __forceinline__ void release(int bar_idx) const {
        if (lane == 0) mbar_arrive(bars + 8 * bar_idx);
    }
    __device__ __forceinline__ void wait_full(int bar_idx, uint32_t parity) const { mbar_wait(bars + 8 * bar_idx, parity); }
    __device__ __forceinline__ void stage(int c, uint32_t parity, uint32_t r0, uint32_t r1, uint32_t r2, uint32_t r3) const {
        if ((c & 3) == 0) mbar_wait(bars + 8 * (BAR_SEMPTY + 2 * wg + (c >> 2)), parity);
        stsm_x4(st_h + c * 2048, r0, r1, r2, r3);
    }
    __device__ __forceinline__ void publish(int block) const {
        fence_async_smem();
        __syncwarp();
        release(BAR_SFULL + 2 * wg + block);
    }
    __device__ __forceinline__ void stage_geglu(int c, uint32_t parity, const uint32_t (&pk)[64]) const {
        const int q = 4 * c;
        stage(c, parity, geglu2(pk[q], pk[32 + q]), geglu2(pk[q + 1], pk[33 + q]), geglu2(pk[q + 2], pk[34 + q]), geglu2(pk[q + 3], pk[35 + q]));
        if ((c & 3) == 3) publish(c >> 2);
    }
    __device__ __forceinline__ void mma_a(float (&acc)[128], int s, bool first = false) const {
        const uint32_t da = desc_lo(base, 16) + s * 1024 + (s & 2) * 4096 + wg * 512;
        const uint32_t db = desc_lo(base + 32768, 8192) + s * 2048;
        wg_fence();
        wgmma_n256<HI_SW>(acc, da, db, first ? 0 : 1);
        wgmma_n256<HI_SW>(acc, da + 2, db + 128, 1);
        wgmma_n256<HI_SW>(acc, da + 4, db + 256, 1);
        wgmma_n256<HI_SW>(acc, da + 6, db + 384, 1);
        wg_commit();
    }
    __device__ __forceinline__ void mma_c(float (&acc)[88], int s, int up, bool first = false) const {
        const uint32_t da = desc_lo(base, 16) + s * 1024 + (s & 2) * 4608 + wg * 512;
        const uint32_t db = desc_lo(base + 32768, 8192) + up * 1536 + s * 3072;
        wg_fence();
        wgmma_n176<HI_SW>(acc, da, db, first ? 0 : 1);
        wgmma_n176<HI_SW>(acc, da + 2, db + 128, 1);
        wgmma_n176<HI_SW>(acc, da + 4, db + 256, 1);
        wgmma_n176<HI_SW>(acc, da + 6, db + 384, 1);
        wg_commit();
    }
    __device__ __forceinline__ void mma_b(float (&acc)[64], int s, bool first = false) const {
        const uint32_t da = desc_lo(base + 16384, 128) + s * 2048 + wg * 128, db = desc_lo(base, 8192) + s * 2048;
        wg_fence();
        wgmma_n128<HI_H>(acc, da, db, first ? 0 : 1);
        wgmma_n128<HI_H>(acc, da + 256, db + 128, 1);
        wgmma_n128<HI_H>(acc, da + 512, db + 256, 1);
        wgmma_n128<HI_H>(acc, da + 768, db + 384, 1);
        wg_commit();
    }
    __device__ __forceinline__ void step_a(float (&acc)[128], int kb) const {
        mma_a(acc, kb & 3);
        release(BAR_EMPTY_A + ((kb - 1) & 3));
    }
    __device__ __forceinline__ void next_a(int kb) const { wait_full(BAR_FULL_A + ((kb + 1) & 3), ((kb + 1) >> 2) & 1); }
};

__global__ void __launch_bounds__(NUM_THREADS, 1) geglu_ffn_kernel(const Ptrs pp, const __grid_constant__ Maps mp) {
    extern __shared__ __align__(1024) uint8_t smem_raw[];
    const int warp = __shfl_sync(0xffffffffu, threadIdx.x >> 5, 0);
    const int lane = threadIdx.x & 31;

    uint32_t sm;
    asm("mov.u32 %0, %%smid;" : "=r"(sm));
    const int tpc = sm >> 1;
    const int q7 = ((tpc - 32) * 37) >> 8;
    const bool extra = (tpc >> 1) == 30;
    const int grp = tpc < 32 ? tpc & 7 : tpc < 60 ? tpc - 31 - 7 * q7 : 0;
    const int j_blk = tpc < 32 ? tpc >> 3 : tpc < 60 ? 4 + q7 : tpc - 58;
    const int m_blk = extra ? (sm & 3) * 4 : grp * 2 + (sm & 1);
    const int col0 = extra ? 54 : j_blk * 2;

    const uint32_t full_c = bars + 8 * BAR_FULL_C, piece = bars + 8 * BAR_PIECE;
    if (warp == 8) {
        if (!extra && elect_one()) {
            const uint32_t b = base + 2 * 65536;
            mbar_init(piece, 1);
            mbar_init(piece + 8, 1);
            mbar_init(piece + 16, 1);
            mbar_init(full_c + 32, 1);
            mbar_init(full_c + 40, 1);
            asm volatile("fence.mbarrier_init.release.cluster;" ::: "memory");
            mbar_expect_tx(piece, 8192 + 6144);
            tma_2d(b + 49152, &mp.x64, piece, 0, m_blk * 128);
            tma_3d(b, &mp.g16, piece, 0, 0, col0);
            tma_3d(b + 4096, &mp.gp16, piece, 0, 0, j_blk);
            mbar_expect_tx(piece + 8, 8192);
            tma_2d(b + 57344, &mp.x64, piece + 8, 0, m_blk * 128 + 64);
            mbar_expect_tx(piece + 16, 6144);
            tma_3d(b + 6144, &mp.g16, piece + 16, 0, 16, col0);
            tma_3d(b + 10240, &mp.gp16, piece + 16, 0, 16, j_blk);
            mbar_expect_tx(full_c + 32, 12288);
            tma_3d(b + 12288, &mp.g16, full_c + 32, 0, 32, col0);
            tma_3d(b + 16384, &mp.gp16, full_c + 32, 0, 32, j_blk);
            tma_3d(b + 18432, &mp.g16, full_c + 32, 0, 48, col0);
            tma_3d(b + 22528, &mp.gp16, full_c + 32, 0, 48, j_blk);
            mbar_expect_tx(full_c + 40, 24576);
            tma_3d(b + 24576, &mp.w64[1], full_c + 40, 0, 0, col0);
            tma_3d(b + 40960, &mp.part[1], full_c + 40, 0, 0, j_blk);
#pragma unroll
            for (int i = 0; i < 4; i++) mbar_init(full_c + 8 * i, 1);
#pragma unroll
            for (int i = 0; i < 6; i++) mbar_init(bars + 8 * (BAR_EMPTY_C + i), 8);
            asm volatile("fence.mbarrier_init.release.cluster;" ::: "memory");
        }
        __syncwarp();
        asm volatile("bar.arrive 4, 384;" ::: "memory");
    } else {
        asm volatile("bar.sync 4, %0;" :: "r"(384) : "memory");
        asm volatile("nanosleep.u32 0;" ::: "memory");
    }

    if (warp < 8) {
        if (warp == 0) {
            if (elect_one()) {
#pragma unroll
                for (int i = 0; i < BAR_FULL_C; i++) {
                    const bool empty = (i >= BAR_EMPTY_A && i < BAR_FULL_B) || (i >= BAR_EMPTY_B && i < BAR_SFULL);
                    mbar_init(bars + 8 * i, empty ? 8 : (i >= BAR_SFULL && i < BAR_SEMPTY) ? 4 : 1);
                }
#pragma unroll
                for (int i = 1; i < 4; i++) mbar_init(bars + 8 * (BAR_POLL + i), 1);
                asm volatile("fence.mbarrier_init.release.cluster;" ::: "memory");
            }
            __syncwarp();
            asm volatile("bar.arrive 2, %0;" :: "r"(extra ? 160 : 128) : "memory");
        }
        asm volatile("setmaxnreg.inc.sync.aligned.u32 240;");
        asm volatile("bar.sync 1, 256;" ::: "memory");
        Consumer c;
        c.lane = lane;
        c.wg = warp >> 2;
        c.st_h = base + STAGING_OFF + c.wg * 16384 + (warp & 3) * 512 + (lane & 8) * 32 + (lane >> 4) * 128 + (lane & 7) * 16;
        const bool always = sm != 0xffffffffu;

        uint32_t pk[64], gp[12], up[12];
        if (extra) {
#pragma unroll
            for (int i = 4; i < 12; i++) asm volatile("" : "=r"(gp[i]), "=r"(up[i]));
#pragma unroll
            for (int i = 0; i < 64; i++) asm volatile("" : "=r"(pk[i]));
            c.wait_full(BAR_FULL_A, 0);
        } else {
            float accg[88], accu[88];
#pragma unroll
            for (int i = 0; i < 88; i++) asm volatile("" : "=f"(accg[i]), "=f"(accu[i]));
            const uint32_t da = desc_lo(base + 2 * 65536 + 49152, 16) + c.wg * 512;
            constexpr uint32_t dq = desc_lo(base + 2 * 65536, 2048);
            c.wait_full(BAR_PIECE + c.wg, 0);
            c.wait_full(BAR_PIECE, 0);
            wg_fence();
            wgmma_n176<HI_SW>(accg, da, dq, 0);
            c.wait_full(BAR_PIECE + 2, 0);
            wg_fence();
            wgmma_n176<HI_SW>(accg, da + 2, dq + 384, 1);
            c.wait_full(BAR_FULL_C + 4, 0);
            wg_fence();
            wgmma_n176<HI_SW>(accg, da + 4, dq + 768, 1);
            wgmma_n176<HI_SW>(accg, da + 6, dq + 1152, 1);
            wg_commit();
            c.wait_full(BAR_FULL_C + 5, 0);
            if (c.wg) asm volatile("bar.sync 6, 256;" ::: "memory");
            c.mma_c(accu, 2, 1, true);
            if (!c.wg) asm volatile("bar.arrive 6, 256;" ::: "memory");
            wg_wait<1>();
            c.release(BAR_EMPTY_C + 4);
            c.wait_full(BAR_FULL_C, 0);
            int s = 0, ps = 2;
            uint32_t ph = 0;
#pragma unroll 1
            for (int kb = 1; kb < 15; kb++) {
                wg_wait<0>();
                c.mma_c(accg, s, 0);
                c.release(BAR_EMPTY_C + 2 * ps + 1);
                c.wait_full(BAR_FULL_C + 2 * s + 1, ph);
                wg_wait<0>();
                c.mma_c(accu, s, 1);
                c.release(BAR_EMPTY_C + 2 * s);
                ps = s;
                if (++s == 3) s = 0;
                if (s == 2) ph ^= 1;
                c.wait_full(BAR_FULL_C + 2 * s, ph);
            }
            wg_wait<0>();
            c.mma_c(accg, 2, 0);
            c.release(BAR_EMPTY_C + 3);
            c.wait_full(BAR_FULL_C + 5, 1);
            c.mma_c(accu, 2, 1);
            wg_wait<1>();
            fence_regs<88>(accg);
            c.release(BAR_EMPTY_C + 4);
#pragma unroll
            for (int i = 0; i < 32; i++) asm volatile("" : "=r"(pk[i]));
#pragma unroll
            for (int i = 0; i < 12; i++) asm volatile("" : "=r"(gp[i]));
            if (always) {
#pragma unroll
                for (int i = 0; i < 12; i++) {
                    gp[i] = i < 4 ? gelu2(accg[64 + 2 * i], accg[65 + 2 * i]) : pack_bf16(accg[64 + 2 * i], accg[65 + 2 * i]);
                    asm volatile("" : "+r"(gp[i]));
                }
#pragma unroll
                for (int i = 0; i < 32; i++) {
                    pk[i] = pack_bf16(accg[2 * i], accg[2 * i + 1]);
                    asm volatile("" : "+r"(pk[i]));
                }
            }
            c.wait_full(BAR_FULL_A, 0);
            wg_wait<0>();
            fence_regs<88>(accu);
            c.release(BAR_EMPTY_C + 5);
#pragma unroll
            for (int i = 0; i < 12; i++) up[i] = pack_bf16(accu[64 + 2 * i], accu[65 + 2 * i]);
            stsm_x4(c.st_h + 8192, mul_bf16x2(gp[0], up[0]), mul_bf16x2(gp[1], up[1]), mul_bf16x2(gp[2], up[2]), mul_bf16x2(gp[3], up[3]));
#pragma unroll
            for (int i = 0; i < 32; i++) pk[32 + i] = pack_bf16(accu[2 * i], accu[2 * i + 1]);
        }

        float acc[128];
#pragma unroll
        for (int i = 0; i < 128; i++) asm volatile("" : "=f"(acc[i]));
        auto stage_part = [&](int i) {
            stsm_x4(c.st_h + 8192 + i * 512, geglu2(gp[i], up[i]), geglu2(gp[i + 1], up[i + 1]), geglu2(gp[i + 2], up[i + 2]), geglu2(gp[i + 3], up[i + 3]));
        };
        c.mma_a(acc, 0, true);
        c.wait_full(BAR_FULL_A + 1, 0);
        c.mma_a(acc, 1);
        if (!extra) stage_part(4);
        wg_wait<1>();
        c.release(BAR_EMPTY_A);
        if (!extra) {
            stage_part(8);
            c.publish(1);
        }
        c.wait_full(BAR_FULL_A + 2, 0);
#pragma unroll 1
        for (int t = extra ? 0 : 2;; t++) {
#pragma unroll
            for (int kb = 2; kb < 10; kb++) {
                wg_wait<0>();
                c.step_a(acc, kb);
                if (t > 0) c.stage_geglu(kb - 2, t & 1, pk);
                c.next_a(kb);
            }
#pragma unroll 1
            for (int kb = 10; kb < 15; kb++) {
                wg_wait<0>();
                c.step_a(acc, kb);
                c.next_a(kb);
            }
            if (t == 3) break;
            c.mma_a(acc, 3);
            wg_wait<1>();
            c.release(BAR_EMPTY_A + 2);
            c.wait_full(BAR_FULL_A, 0);
            wg_wait<0>();
            fence_regs<128>(acc);
            c.release(BAR_EMPTY_A + 3);
#pragma unroll
            for (int i = 0; i < 64; i++) pk[i] = pack_bf16(acc[2 * i], acc[2 * i + 1]);
            c.mma_a(acc, 0, true);
            c.wait_full(BAR_FULL_A + 1, 0);
            c.mma_a(acc, 1);
            wg_wait<1>();
            c.release(BAR_EMPTY_A);
            c.wait_full(BAR_FULL_A + 2, 0);
        }
        wg_wait<0>();
        c.step_a(acc, 15);
        auto stage_acc = [&](int q) {
            const int g = 8 * q, u = 64 + 8 * q;
            c.stage(q, 0, pack_bf16(geglu(acc[g], acc[u]), geglu(acc[g + 1], acc[u + 1])), pack_bf16(geglu(acc[g + 2], acc[u + 2]), geglu(acc[g + 3], acc[u + 3])),
                    pack_bf16(geglu(acc[g + 4], acc[u + 4]), geglu(acc[g + 5], acc[u + 5])), pack_bf16(geglu(acc[g + 6], acc[u + 6]), geglu(acc[g + 7], acc[u + 7])));
        };
        if (extra) {
            wg_wait<0>();
            fence_regs<128>(acc);
#pragma unroll
            for (int q = 0; q < 8; q++) {
                stage_acc(q);
                if ((q & 3) == 3) c.publish(q >> 2);
            }
            return;
        }
        c.wait_full(BAR_FULL_B, 0);

        constexpr int KB0 = 17;
        float acc4[64];
        uint32_t h0, h1;
#pragma unroll
        for (int kb = 0; kb < KB0; kb++) {
            wg_wait<0>();
            if (kb == 0) fence_regs<128>(acc);
            c.mma_b(acc4, kb % STB, kb == 0);
            c.release(kb == 0 ? BAR_EMPTY_A + 3 : BAR_EMPTY_B + (kb - 1) % STB);
            if (!(kb & 1)) asm volatile("" : "=r"(h0), "=r"(h1));
            if (always) {
                if (kb % 8 == 0 && kb) c.publish(kb / 8 - 1);
                if (kb < 16) {
                    const int g = 4 * kb, u = 64 + g;
                    const uint32_t r0 = pack_bf16(geglu(acc[g], acc[u]), geglu(acc[g + 1], acc[u + 1]));
                    const uint32_t r1 = pack_bf16(geglu(acc[g + 2], acc[u + 2]), geglu(acc[g + 3], acc[u + 3]));
                    if (kb & 1) {
                        c.stage(kb >> 1, 0, h0, h1, r0, r1);
                    } else {
                        h0 = r0;
                        h1 = r1;
                        asm volatile("" : "+r"(h0), "+r"(h1));
                    }
                }
            }
            c.wait_full(BAR_FULL_B + (kb + 1) % STB, ((kb + 1) / STB) & 1);
        }
        int s = KB0 % STB, ps = (KB0 - 1) % STB;
        uint32_t ph = (KB0 / STB) & 1;
#pragma unroll 1
        for (int kb = KB0; kb < KB_FF - TN; kb++) {
            wg_wait<0>();
            c.mma_b(acc4, s);
            c.release(BAR_EMPTY_B + ps);
            ps = s;
            if (++s == STB) { s = 0; ph ^= 1; }
            c.wait_full(BAR_FULL_B + s, ph);
        }
        c.wait_full(BAR_SEMPTY + 2 * c.wg, 1);
        c.wait_full(BAR_SEMPTY + 2 * c.wg + 1, 1);
        const uint32_t strip = base + STAGING_OFF + c.wg * 16384 + (warp & 3) * 2048;
        const uint32_t st_row = strip + (lane & 15) * 128, st_sw = ((lane >> 4) ^ (lane & 7)) << 4;
        const int row0 = m_blk * 128 + warp * 16;
        const uint32_t ld_row = base + STAGING_OFF + 16384 + (warp & 3) * 2048 + (lane >> 3) * 128 + (((lane & 7) ^ (lane >> 3)) << 4);
        uint8_t* optr = pp.o + (size_t)((row0 | 64) + (lane >> 3)) * 2048 + j_blk * 256 + (lane & 7) * 16;
        auto stage_out = [&](int h) {
#pragma unroll
            for (int q = 0; q < 4; q++) {
                const int i = 32 * h + 8 * q;
                stsm_x4(st_row + h * 8192 + (st_sw ^ (q << 5)), pack_bf16(acc4[i], acc4[i + 1]), pack_bf16(acc4[i + 2], acc4[i + 3]),
                        pack_bf16(acc4[i + 4], acc4[i + 5]), pack_bf16(acc4[i + 6], acc4[i + 7]));
            }
        };
        auto store_out = [&](int h) {
            uint4 v[4];
#pragma unroll
            for (int i = 0; i < 4; i++)
                asm volatile("ld.shared.v4.u32 {%0, %1, %2, %3}, [%4];" : "=r"(v[i].x), "=r"(v[i].y), "=r"(v[i].z), "=r"(v[i].w)
                             : "r"((ld_row ^ ((i & 1) << 6)) + i * 512 + h * 8192) : "memory");
#pragma unroll
            for (int i = 0; i < 4; i++)
                asm volatile("st.global.v4.u32 [%0], {%1, %2, %3, %4};" :: "l"(optr + i * 8192 + h * 128), "r"(v[i].x), "r"(v[i].y), "r"(v[i].z), "r"(v[i].w) : "memory");
        };
        wg_wait<0>();
        if (!c.wg) {
#pragma unroll
            for (int kb = KB_FF - TN; kb < KB_FF; kb++) {
                if (kb > KB_FF - TN) c.wait_full(BAR_FULL_B + kb % STB, (kb / STB) & 1);
                c.mma_b(acc4, kb % STB);
            }
            asm volatile("bar.arrive 6, 256;" ::: "memory");
            wg_wait<0>();
            fence_regs<64>(acc4);
#pragma unroll
            for (int h = 0; h < 2; h++) {
                stage_out(h);
                fence_async_smem();
                __syncwarp();
                if (elect_one()) {
                    tma_store_2d(&mp.out, strip + h * 8192, j_blk * 128 + h * 64, row0);
                    bulk_commit();
                }
            }
            asm volatile("bar.sync %0, 64;" :: "r"(7 + warp) : "memory");
            if (elect_one()) {
                fence_async_smem();
                tma_store_2d(&mp.out, strip + 16384, j_blk * 128, row0 + 64);
                bulk_commit();
            }
            if (elect_one()) asm volatile("cp.async.bulk.wait_group.read 0;" ::: "memory");
            __syncwarp();
        } else {
            float half[2][32];
            uint32_t af[16 * TR];
            const uint32_t ld_h = c.st_h - STAGING_OFF + 2048;
#pragma unroll
            for (int kb = KB_FF - TN; kb < KB_FF; kb++) {
                if (kb > KB_FF - TN) c.wait_full(BAR_FULL_B + kb % STB, (kb / STB) & 1);
#pragma unroll
                for (int q = 4 * (kb - KB_FF + TR); q >= 0 && q < 4 * (kb + 1 - KB_FF + TR); q++)
                    asm volatile("ldmatrix.sync.aligned.m8n8.x4.shared.b16 {%0, %1, %2, %3}, [%4];"
                                 : "=r"(af[4 * q]), "=r"(af[4 * q + 1]), "=r"(af[4 * q + 2]), "=r"(af[4 * q + 3])
                                 : "r"(ld_h + (kb % STB) * 32768 + (q & 3) * 4096) : "memory");
            }
            auto mma_half = [&](int h, int q0, int q1) {
                wg_fence();
#pragma unroll
                for (int q = q0; q < q1; q++)
                    wgmma_n64_rs(half[h], af + 4 * q, desc_lo(base, 8192) + ((KB_FF - TR + (q >> 2)) % STB) * 2048 + h * 512 + (q & 3) * 128, h | q);
                wg_commit();
            };
            auto merge_half = [&](int h) {
                fence_regs<32>(half[h]);
#pragma unroll
                for (int i = 0; i < 32; i++) acc4[32 * h + i] = h ? half[h][i] : acc4[32 * h + i] + half[h][i];
            };
            asm volatile("bar.sync 6, 256;" ::: "memory");
#pragma unroll
            for (int kb = KB_FF - TN; kb < KB_FF - TR; kb++) c.mma_b(acc4, kb % STB);
            mma_half(0, 0, 4 * TR);
            wg_wait<1>();
            fence_regs<64>(acc4);
#pragma unroll
            for (int i = 0; i < 32; i++) asm volatile("mov.f32 %0, %1;" : "=f"(half[1][i]) : "f"(acc4[32 + i]));
            mma_half(1, 0, RB);
            wg_wait<1>();
            merge_half(0);
            stage_out(0);
            mma_half(1, RB, 4 * TR);
            asm volatile("bar.arrive %0, 64;" :: "r"(3 + warp) : "memory");
            wg_wait<0>();
            merge_half(1);
            stage_out(1);
            __syncwarp();
            store_out(1);
        }
    } else {
        asm volatile("setmaxnreg.dec.sync.aligned.u32 24;");
        if (warp != 8) {
            asm volatile("bar.sync 2, %0;" :: "r"(extra ? 160 : 128) : "memory");
            uint32_t cnt;
            if (warp == 11) asm volatile("ld.relaxed.gpu.global.u32 %0, [%1];" : "=r"(cnt) : "l"(g_ready + m_blk * 4) : "memory");
            asm volatile("bar.sync 5, 96;" ::: "memory");
            if (elect_one()) {
                if (warp <= 10) {
                    const int w = warp - 9;
                    if (!extra) mbar_arrive(bars + 8 * (BAR_SEMPTY + 2 * w));
#pragma unroll 1
                    for (int b = extra ? 0 : 1; b < 8; b++) {
                        const int t = b >> 1;
                        const bool part = !extra && b == 1;
                        const int m = extra ? m_blk + t : m_blk;
                        const int chunk = part ? 64 + 3 * j_blk : (col0 + (b & 1) + (extra || t == 1 ? 0 : 16 * t - 10)) * 4;
                        uint8_t* dst = g_h + ((size_t)m * (KB_FF * 4) + chunk) * 4096 + w * 2048;
                        const uint32_t src = base + STAGING_OFF + w * 16384 + (b & 1) * 8192;
                        const uint32_t pace = t < 3 ? 300 : 0;
                        mbar_wait_p(bars + 8 * (BAR_SFULL + 2 * w + (b & 1)), (extra ? t : t + b + 1) & 1);
#pragma unroll 1
                        for (int q = 0; q < (part ? 3 : 4); q++) {
                            if (q | (b & 1)) __nanosleep(pace);
                            bulk_store(dst + q * 4096, src + q * 2048, 2048);
                            bulk_commit();
                            asm volatile("cp.async.bulk.wait_group.read 0;" ::: "memory");
                        }
                        mbar_arrive(bars + 8 * (BAR_SEMPTY + 2 * w + (b & 1)));
                        if ((b & 1) && !part) {
                            asm volatile("cp.async.bulk.wait_group 0;" ::: "memory");
                            asm volatile("fence.proxy.async.global;" ::: "memory");
                            asm volatile("red.release.gpu.global.add.u32 [%0], %1;"
                                         :: "l"(g_ready + m * 4 + (extra ? 3 : t - 1)), "r"(extra ? 16 : 2) : "memory");
                        }
                    }
                } else {
                    uint32_t nsm;
                    asm("mov.u32 %0, %%nsmid;" : "=r"(nsm));
                    if (smem_u32(smem_raw) != base || nsm != NUM_CTAS) __trap();
                    prefetch_map(&mp.d);
                    prefetch_map(&mp.out);
                    if (extra) return;
                    const int row = m_blk * 64 + j_blk * 8;
#pragma unroll 1
                    for (int t = 0; t < 2; t++) {
                        mbar_wait_p(bars + 8 * (BAR_PF + t), 0);
#pragma unroll 1
                        for (int r = (row + 768 - 256 * t) & 1023, e = r + 8; r < e; r++) {
                            prefetch_l2(pp.wg + r * (D_FF * 2) + 2816 + t * 2048, 2048);
                            prefetch_l2(pp.wu + r * (D_FF * 2) + 2816 + t * 2048, 2048);
                        }
                    }
                    mbar_wait_p(bars + 8 * (BAR_PF + 2), 0);
                    prefetch_l2(pp.wd + row * 2048, 16384);
#pragma unroll 1
                    for (int round = 0; round < 4; round++) {
                        uint32_t v, it = 0;
                        if (round) mbar_wait_p(bars + 8 * (BAR_POLL + round), 0);
                        while (true) {
                            asm volatile("ld.acquire.gpu.global.u32 %0, [%1];" : "=r"(v) : "l"(g_ready + m_blk * 4 + round) : "memory");
                            if (v - (cnt & ~31u) >= 32u) break;
                            if (++it > (1u << 20)) __trap();
                            __nanosleep(200);
                        }
                        asm volatile("fence.proxy.async.global;" ::: "memory");
                        mbar_arrive(bars + 8 * (BAR_HREADY + round));
                    }
                }
            }
            return;
        }
        if (extra) asm volatile("bar.sync 2, 160;" ::: "memory");
        if (!elect_one()) return;
        if (extra) __nanosleep(2000);
        if (!extra) {
            int s = 0;
            uint32_t ph = 1;
#pragma unroll 1
            for (int i = 2; i < 32; i++) {
                const uint32_t full = full_c + 8 * s, bx = base + (s >> 1) * 16384 + (s & 4) * 36864;
                const uint32_t bw = base + 32768 + s * 24576;
                if (s == 4) ph ^= 1;
                mbar_wait_p(bars + 8 * (BAR_EMPTY_C + s), ph);
                if (i & 1) tma_2d(bx, &mp.x128, full - 8, (i >> 1) * 64, m_blk * 128);
                mbar_expect_tx(full, (i & 1) ? 24576 : 40960);
                tma_3d(bw, &mp.w64[i & 1], full, 0, (i >> 1) * 64, col0);
                tma_3d(bw + 16384, &mp.part[i & 1], full, 0, (i >> 1) * 64, j_blk);
                if (i == 8 + ((3 * m_blk) >> 1)) mbar_arrive(bars + 8 * BAR_PF);
                if (++s == 6) s = 0;
            }
        }
#pragma unroll 1
        for (int i = 0; i < (extra ? 64 : 32); i++) {
            const int s = i & 3, t = i >> 4, k0 = ((((i & 12) | ((0xc9 >> 2 * s) & 3)) + 12 - 4 * t) & 15) * 64;
            const bool keep = !extra && (i == 1 || (i >> 2) == 4 || i == 0 || i == 3);
            const int c0 = extra ? col0 : col0 + 16 * t + 22;
            const uint32_t full = bars + 8 * (BAR_FULL_A + s), b = base + 32768 + s * 32768;
            if (i < 4 && !extra) {
                if (i < 3) mbar_wait_p(bars + 8 * (BAR_EMPTY_C + i + 1), 0);
            } else {
                mbar_wait_p(bars + 8 * (BAR_EMPTY_A + s), ((i >> 2) & 1) ^ 1);
            }
            mbar_expect_tx(full, keep ? 32768 : 49152);
            tma_3d(b, &mp.w64[0], full, 0, k0, c0);
            tma_3d(b + 16384, &mp.w64[1], full, 0, k0, c0);
            if (i == 2 && !extra) mbar_wait_p(bars + 8 * (BAR_EMPTY_C + 5), 1);
            if (!keep) tma_2d(base + s * 16384 + (s & 2) * 65536, &mp.x128, full, k0, (extra ? m_blk + t : m_blk) * 128);
            if (i == 4 + m_blk) mbar_arrive(bars + 8 * (BAR_PF + 1));
            if (i == 20 + (m_blk >> 1)) mbar_arrive(bars + 8 * (BAR_PF + 2));
        }
        if (extra) return;
        const uint8_t* h_src = g_h + (size_t)m_blk * KB_FF * 16384;
        int s = 0;
        uint32_t ph = 1;
#pragma unroll 1
        for (int i = 0; i < KB_FF; i++) {
            const uint32_t full = bars + 8 * (BAR_FULL_B + s);
            if (i < STB) mbar_wait_p(bars + 8 * (BAR_EMPTY_A + (i == 0 ? 1 : (2 * i + 1) / 3)), 1);
            else mbar_wait_p(bars + 8 * (BAR_EMPTY_B + s), ph);
            mbar_expect_tx(full, 32768);
            tma_3d(base + s * 32768, &mp.d, full, 0, i * 64, col0);
            if (i == 0 || (i & 15) == 6) mbar_wait_p(bars + 8 * (BAR_HREADY + (i >> 4)), 0);
            bulk_load(base + s * 32768 + 16384, h_src + (size_t)i * 16384, 16384, full);
            if (i >= 16 && (i & 15) == 2) mbar_arrive(bars + 8 * (BAR_POLL + (i >> 4)));
            if (++s == STB) { s = 0; ph ^= 1; }
        }
    }
}

typedef CUresult (*EncodeFn)(CUtensorMap*, CUtensorMapDataType, cuuint32_t, void*, const cuuint64_t*, const cuuint64_t*,
                             const cuuint32_t*, const cuuint32_t*, CUtensorMapInterleave, CUtensorMapSwizzle,
                             CUtensorMapL2promotion, CUtensorMapFloatOOBfill);

void map_2d(EncodeFn enc, CUtensorMap* m, const void* p, int rows, int cols, int box_rows) {
    cuuint64_t dims[2] = {(cuuint64_t)cols, (cuuint64_t)rows};
    cuuint64_t str[1] = {(cuuint64_t)cols * 2};
    cuuint32_t box[2] = {64, (cuuint32_t)box_rows};
    cuuint32_t es[2] = {1, 1};
    enc(m, CU_TENSOR_MAP_DATA_TYPE_BFLOAT16, 2, const_cast<void*>(p), dims, str, box, es, CU_TENSOR_MAP_INTERLEAVE_NONE,
        CU_TENSOR_MAP_SWIZZLE_128B, CU_TENSOR_MAP_L2_PROMOTION_L2_128B, CU_TENSOR_MAP_FLOAT_OOB_FILL_NONE);
}
void map_w(EncodeFn enc, CUtensorMap* m, const void* p, int K, int N, int rows, int atoms) {
    cuuint64_t dims[3] = {64, (cuuint64_t)K, (cuuint64_t)N / 64};
    cuuint64_t str[2] = {(cuuint64_t)N * 2, 128};
    cuuint32_t box[3] = {64, (cuuint32_t)rows, (cuuint32_t)atoms};
    cuuint32_t es[3] = {1, 1, 1};
    enc(m, CU_TENSOR_MAP_DATA_TYPE_BFLOAT16, 3, const_cast<void*>(p), dims, str, box, es, CU_TENSOR_MAP_INTERLEAVE_NONE,
        CU_TENSOR_MAP_SWIZZLE_128B, CU_TENSOR_MAP_L2_PROMOTION_L2_128B, CU_TENSOR_MAP_FLOAT_OOB_FILL_NONE);
}

void map_part(EncodeFn enc, CUtensorMap* m, const void* p, int rows) {
    cuuint64_t dims[3] = {48, (cuuint64_t)D_MODEL, 8};
    cuuint64_t str[2] = {(cuuint64_t)D_FF * 2, 96};
    cuuint32_t box[3] = {64, (cuuint32_t)rows, 1};
    cuuint32_t es[3] = {1, 1, 1};
    enc(m, CU_TENSOR_MAP_DATA_TYPE_BFLOAT16, 3, (char*)const_cast<void*>(p) + 1024 * 2, dims, str, box, es, CU_TENSOR_MAP_INTERLEAVE_NONE,
        CU_TENSOR_MAP_SWIZZLE_128B, CU_TENSOR_MAP_L2_PROMOTION_L2_128B, CU_TENSOR_MAP_FLOAT_OOB_FILL_NONE);
}

}

extern "C" void kernel_launch(void* const* d_in, const int* in_sizes, int n_in, void* d_out, int out_size) {
    (void)in_sizes; (void)n_in; (void)out_size;
    void* fn = nullptr;
    cudaDriverEntryPointQueryResult st;
    cudaGetDriverEntryPoint("cuTensorMapEncodeTiled", &fn, cudaEnableDefault, &st);
    EncodeFn enc = (EncodeFn)fn;
    Maps mp;
    map_2d(enc, &mp.x64, d_in[0], M_TOK, D_MODEL, 64);
    map_2d(enc, &mp.x128, d_in[0], M_TOK, D_MODEL, 128);
    map_w(enc, &mp.g16, d_in[1], D_MODEL, D_FF, 16, 2);
    map_part(enc, &mp.gp16, d_in[1], 16);
    map_w(enc, &mp.w64[0], d_in[1], D_MODEL, D_FF, 64, 2);
    map_w(enc, &mp.w64[1], d_in[2], D_MODEL, D_FF, 64, 2);
    map_part(enc, &mp.part[0], d_in[1], 64);
    map_part(enc, &mp.part[1], d_in[2], 64);
    map_w(enc, &mp.d, d_in[3], D_FF, D_MODEL, 64, 2);
    map_2d(enc, &mp.out, d_out, M_TOK, D_MODEL, 16);
    const Ptrs pp = {(const uint8_t*)d_in[1], (const uint8_t*)d_in[2], (const uint8_t*)d_in[3], (uint8_t*)d_out};
    cudaFuncSetAttribute(geglu_ffn_kernel, cudaFuncAttributeMaxDynamicSharedMemorySize, SMEM_BYTES);
    geglu_ffn_kernel<<<NUM_CTAS, NUM_THREADS, SMEM_BYTES>>>(pp, mp);
}
```

```cpp
#include <cuda_runtime.h>
#include <cuda_bf16.h>
#include <cuda.h>
#include <stdint.h>

namespace {

constexpr int M_TOK = 2048, D_MODEL = 1024, D_FF = 3584;
constexpr int KB_FF = D_FF / 64;
constexpr int NUM_CTAS = 132;
constexpr int NUM_THREADS = 384;

constexpr int STB = 6;
constexpr int RING_BYTES = 196608;
constexpr int STAGING_OFF = RING_BYTES;
constexpr int BAR_OFF = STAGING_OFF + 32768;
constexpr int SMEM_BYTES = BAR_OFF + 512;
constexpr uint32_t base = 1024, bars = base + BAR_OFF;

constexpr int BAR_FULL_A = 0, BAR_EMPTY_A = 4, BAR_FULL_B = 8, BAR_EMPTY_B = 14, BAR_SFULL = 20, BAR_SEMPTY = 24,
              BAR_HREADY = 28, BAR_PF = 32, BAR_FULL_C = 35, BAR_EMPTY_C = 41, BAR_PIECE = 47, BAR_POLL = 49;

__device__ __align__(1024) uint8_t g_h[(size_t)M_TOK * D_FF * 2];
__device__ __align__(16) unsigned int g_ready[16 * 4];

__device__ __forceinline__ uint32_t smem_u32(const void* p) { return (uint32_t)__cvta_generic_to_shared(p); }
__device__ __forceinline__ bool elect_one() {
    uint32_t p;
    asm volatile("{\n.reg .pred p;\nelect.sync _|p, 0xffffffff;\nselp.u32 %0, 1, 0, p;\n}" : "=r"(p));
    return p != 0;
}
__device__ __forceinline__ void mbar_init(uint32_t bar, uint32_t cnt) {
    asm volatile("mbarrier.init.shared::cta.b64 [%0], %1;" :: "r"(bar), "r"(cnt) : "memory");
}
__device__ __forceinline__ void mbar_expect_tx(uint32_t bar, uint32_t bytes) {
    asm volatile("mbarrier.arrive.expect_tx.shared::cta.b64 _, [%0], %1;" :: "r"(bar), "r"(bytes) : "memory");
}
__device__ __forceinline__ void mbar_arrive(uint32_t bar) {
    asm volatile("mbarrier.arrive.shared::cta.b64 _, [%0];" :: "r"(bar) : "memory");
}
__device__ __forceinline__ bool mbar_try(uint32_t bar, uint32_t parity) {
    uint32_t done;
    asm volatile("{\n.reg .pred p;\nmbarrier.try_wait.parity.shared::cta.b64 p, [%1], %2;\nselp.u32 %0, 1, 0, p;\n}"
                 : "=r"(done) : "r"(bar), "r"(parity) : "memory");
    return done != 0;
}
__device__ __forceinline__ void mbar_wait_p(uint32_t bar, uint32_t parity) {
    uint32_t it = 0;
#pragma unroll 1
    while (!mbar_try(bar, parity)) {
        if (++it > (1u << 20)) __trap();
    }
}
__device__ __forceinline__ void mbar_wait(uint32_t bar, uint32_t parity) {
    if (mbar_try(bar, parity)) return;
    uint32_t it = 0;
#pragma unroll 1
    while (!mbar_try(bar, parity)) {
        if (++it > (1u << 21)) break;
    }
}
__device__ __forceinline__ void tma_2d(uint32_t dst, const CUtensorMap* m, uint32_t bar, int c0, int c1) {
    asm volatile("cp.async.bulk.tensor.2d.shared::cluster.global.mbarrier::complete_tx::bytes [%0], [%1, {%3, %4}], [%2];"
                 :: "r"(dst), "l"((uint64_t)m), "r"(bar), "r"(c0), "r"(c1) : "memory");
}
__device__ __forceinline__ void tma_3d(uint32_t dst, const CUtensorMap* m, uint32_t bar, int c0, int c1, int c2) {
    asm volatile("cp.async.bulk.tensor.3d.shared::cluster.global.mbarrier::complete_tx::bytes [%0], [%1, {%3, %4, %5}], [%2];"
                 :: "r"(dst), "l"((uint64_t)m), "r"(bar), "r"(c0), "r"(c1), "r"(c2) : "memory");
}
__device__ __forceinline__ void bulk_load(uint32_t dst, const void* src, uint32_t bytes, uint32_t bar) {
    asm volatile("cp.async.bulk.shared::cluster.global.mbarrier::complete_tx::bytes [%0], [%1], %2, [%3];"
                 :: "r"(dst), "l"(src), "r"(bytes), "r"(bar) : "memory");
}
__device__ __forceinline__ void bulk_store(void* dst, uint32_t src, uint32_t bytes) {
    asm volatile("cp.async.bulk.global.shared::cta.bulk_group [%0], [%1], %2;" :: "l"(dst), "r"(src), "r"(bytes) : "memory");
}
__device__ __forceinline__ void tma_store_2d(const CUtensorMap* m, uint32_t src, int c0, int c1) {
    asm volatile("cp.async.bulk.tensor.2d.global.shared::cta.bulk_group [%0, {%2, %3}], [%1];"
                 :: "l"((uint64_t)m), "r"(src), "r"(c0), "r"(c1) : "memory");
}
__device__ __forceinline__ void prefetch_map(const CUtensorMap* m) {
    asm volatile("prefetch.tensormap [%0];" :: "l"((uint64_t)m) : "memory");
}
__device__ __forceinline__ void prefetch_l2(const void* p, uint32_t bytes) {
    asm volatile("cp.async.bulk.prefetch.L2.global [%0], %1;" :: "l"(p), "r"(bytes) : "memory");
}
__device__ __forceinline__ void bulk_commit() { asm volatile("cp.async.bulk.commit_group;" ::: "memory"); }
__device__ __forceinline__ void fence_async_smem() { asm volatile("fence.proxy.async.shared::cta;" ::: "memory"); }
__device__ __forceinline__ void wg_fence() { asm volatile("wgmma.fence.sync.aligned;" ::: "memory"); }
__device__ __forceinline__ void wg_commit() { asm volatile("wgmma.commit_group.sync.aligned;" ::: "memory"); }
template <int N> __device__ __forceinline__ void wg_wait() { asm volatile("wgmma.wait_group.sync.aligned %0;" :: "n"(N) : "memory"); }

constexpr uint32_t HI_SW = (1u << 30) | 64u, HI_H = 16u;
__host__ __device__ constexpr uint32_t desc_lo(uint32_t addr, uint32_t lbo) { return (addr >> 4) | ((lbo >> 4) << 16); }

#define R8(a, o) "+f"(a[o + 0]), "+f"(a[o + 1]), "+f"(a[o + 2]), "+f"(a[o + 3]), "+f"(a[o + 4]), "+f"(a[o + 5]), "+f"(a[o + 6]), "+f"(a[o + 7])
#define R32(a, o) R8(a, o), R8(a, o + 8), R8(a, o + 16), R8(a, o + 24)

template <uint32_t HA, int O = 0, int N>
__device__ __forceinline__ void wgmma_n256(float (&d)[N], uint32_t da, uint32_t db, int scale_d) {
    asm volatile("{\n.reg .pred p;\n.reg .b64 da, db;\nsetp.ne.b32 p, %130, 0;\nmov.b64 da, {%128, %131};\nmov.b64 db, {%129, %132};\n"
        "wgmma.mma_async.sync.aligned.m64n256k16.f32.bf16.bf16 "
        "{%0,%1,%2,%3,%4,%5,%6,%7,%8,%9,%10,%11,%12,%13,%14,%15,%16,%17,%18,%19,%20,%21,%22,%23,%24,%25,%26,%27,%28,%29,%30,%31,"
        "%32,%33,%34,%35,%36,%37,%38,%39,%40,%41,%42,%43,%44,%45,%46,%47,%48,%49,%50,%51,%52,%53,%54,%55,%56,%57,%58,%59,%60,%61,%62,%63,"
        "%64,%65,%66,%67,%68,%69,%70,%71,%72,%73,%74,%75,%76,%77,%78,%79,%80,%81,%82,%83,%84,%85,%86,%87,%88,%89,%90,%91,%92,%93,%94,%95,"
        "%96,%97,%98,%99,%100,%101,%102,%103,%104,%105,%106,%107,%108,%109,%110,%111,%112,%113,%114,%115,%116,%117,%118,%119,%120,%121,%122,%123,%124,%125,%126,%127},"
        " da, db, p, 1, 1, 0, 1;\n}\n"
        : R32(d, O + 0), R32(d, O + 32), R32(d, O + 64), R32(d, O + 96)
        : "r"(da), "r"(db), "r"(scale_d), "n"(HA), "n"(HI_SW));
}
template <uint32_t HA, int O = 0, int N>
__device__ __forceinline__ void wgmma_n176(float (&d)[N], uint32_t da, uint32_t db, int scale_d) {
    asm volatile("{\n.reg .pred p;\n.reg .b64 da, db;\nsetp.ne.b32 p, %90, 0;\nmov.b64 da, {%88, %91};\nmov.b64 db, {%89, %92};\n"
        "wgmma.mma_async.sync.aligned.m64n176k16.f32.bf16.bf16 "
        "{%0,%1,%2,%3,%4,%5,%6,%7,%8,%9,%10,%11,%12,%13,%14,%15,%16,%17,%18,%19,%20,%21,%22,%23,%24,%25,%26,%27,%28,%29,%30,%31,"
        "%32,%33,%34,%35,%36,%37,%38,%39,%40,%41,%42,%43,%44,%45,%46,%47,%48,%49,%50,%51,%52,%53,%54,%55,%56,%57,%58,%59,%60,%61,%62,%63,"
        "%64,%65,%66,%67,%68,%69,%70,%71,%72,%73,%74,%75,%76,%77,%78,%79,%80,%81,%82,%83,%84,%85,%86,%87},"
        " da, db, p, 1, 1, 0, 1;\n}\n"
        : R32(d, O + 0), R32(d, O + 32), R8(d, O + 64), R8(d, O + 72), R8(d, O + 80)
        : "r"(da), "r"(db), "r"(scale_d), "n"(HA), "n"(HI_SW));
}
template <uint32_t HA, int O = 0, int N>
__device__ __forceinline__ void wgmma_n128(float (&d)[N], uint32_t da, uint32_t db, int scale_d) {
    asm volatile("{\n.reg .pred p;\n.reg .b64 da, db;\nsetp.ne.b32 p, %66, 0;\nmov.b64 da, {%64, %67};\nmov.b64 db, {%65, %68};\n"
        "wgmma.mma_async.sync.aligned.m64n128k16.f32.bf16.bf16 "
        "{%0,%1,%2,%3,%4,%5,%6,%7,%8,%9,%10,%11,%12,%13,%14,%15,%16,%17,%18,%19,%20,%21,%22,%23,%24,%25,%26,%27,%28,%29,%30,%31,"
        "%32,%33,%34,%35,%36,%37,%38,%39,%40,%41,%42,%43,%44,%45,%46,%47,%48,%49,%50,%51,%52,%53,%54,%55,%56,%57,%58,%59,%60,%61,%62,%63},"
        " da, db, p, 1, 1, 0, 1;\n}\n"
        : R32(d, O + 0), R32(d, O + 32)
        : "r"(da), "r"(db), "r"(scale_d), "n"(HA), "n"(HI_SW));
}
__device__ __forceinline__ void wgmma_n64_rs(float (&d)[32], const uint32_t* a, uint32_t db, int scale_d) {
    asm volatile("{\n.reg .pred p;\n.reg .b64 db;\nsetp.ne.b32 p, %37, 0;\nmov.b64 db, {%36, %38};\n"
        "wgmma.mma_async.sync.aligned.m64n64k16.f32.bf16.bf16 "
        "{%0,%1,%2,%3,%4,%5,%6,%7,%8,%9,%10,%11,%12,%13,%14,%15,%16,%17,%18,%19,%20,%21,%22,%23,%24,%25,%26,%27,%28,%29,%30,%31},"
        " {%32,%33,%34,%35}, db, p, 1, 1, 1;\n}\n"
        : R32(d, 0)
        : "r"(a[0]), "r"(a[1]), "r"(a[2]), "r"(a[3]), "r"(db), "r"(scale_d), "n"(HI_SW));
}
template <int M, int N> __device__ __forceinline__ void fence_regs(float (&d)[N]) {
#pragma unroll
    for (int i = 0; i < M; i++) asm volatile("" : "+f"(d[i]) :: "memory");
}

__device__ __forceinline__ uint32_t pack_bf16(float lo, float hi) {
    uint32_t r;
    asm("cvt.rn.bf16x2.f32 %0, %1, %2;" : "=r"(r) : "f"(hi), "f"(lo));
    return r;
}
__device__ __forceinline__ float gelu_gate(float g) {
    const float K0 = -2.3022081986f;
    const float K1 = -0.1029432397f;
    float t = g * fmaf(g * g, K1, K0);
    float e, r;
    asm("ex2.approx.ftz.f32 %0, %1;" : "=f"(e) : "f"(t));
    asm("rcp.approx.ftz.f32 %0, %1;" : "=f"(r) : "f"(1.0f + e));
    return r;
}
__device__ __forceinline__ float geglu(float g, float u) { return (g * u) * gelu_gate(g); }
__device__ __forceinline__ uint32_t gelu2(float lo, float hi) { return pack_bf16(lo * gelu_gate(lo), hi * gelu_gate(hi)); }
__device__ __forceinline__ uint32_t mul_bf16x2(uint32_t a, uint32_t b) {
    uint32_t r;
    asm("mul.rn.bf16x2 %0, %1, %2;" : "=r"(r) : "r"(a), "r"(b));
    return r;
}
__device__ __forceinline__ uint32_t geglu2(uint32_t g, uint32_t u) {
    float lo = geglu(__uint_as_float(g << 16), __uint_as_float(u << 16));
    float hi = geglu(__uint_as_float(g & 0xffff0000u), __uint_as_float(u & 0xffff0000u));
    return pack_bf16(lo, hi);
}
__device__ __forceinline__ void stsm_x4(uint32_t addr, uint32_t r0, uint32_t r1, uint32_t r2, uint32_t r3) {
    asm volatile("stmatrix.sync.aligned.m8n8.x4.shared.b16 [%0], {%1, %2, %3, %4};"
                 :: "r"(addr), "r"(r0), "r"(r1), "r"(r2), "r"(r3) : "memory");
}

constexpr int TN = 5, TR = 4, RB = 9;
struct Maps { CUtensorMap x64, g16, gp16, w64[2], part[2], x128, d, out; };
struct Ptrs { const uint8_t *wg, *wu, *wd; uint8_t* o; const uint8_t* x; };

struct Consumer {
    uint32_t st_h;
    int lane, wg;

    __device__ __forceinline__ void release(int bar_idx) const {
        if (lane == 0) mbar_arrive(bars + 8 * bar_idx);
    }
    __device__ __forceinline__ void wait_full(int bar_idx, uint32_t parity) const { mbar_wait(bars + 8 * bar_idx, parity); }
    __device__ __forceinline__ void stage(int c, uint32_t parity, uint32_t r0, uint32_t r1, uint32_t r2, uint32_t r3) const {
        if ((c & 3) == 0) mbar_wait(bars + 8 * (BAR_SEMPTY + 2 * wg + (c >> 2)), parity);
        stsm_x4(st_h + c * 2048, r0, r1, r2, r3);
    }
    __device__ __forceinline__ void publish(int block) const {
        fence_async_smem();
        __syncwarp();
        release(BAR_SFULL + 2 * wg + block);
    }
    __device__ __forceinline__ void stage_geglu(int c, uint32_t parity, const uint32_t (&pk)[64]) const {
        const int q = 4 * c;
        stage(c, parity, geglu2(pk[q], pk[32 + q]), geglu2(pk[q + 1], pk[33 + q]), geglu2(pk[q + 2], pk[34 + q]), geglu2(pk[q + 3], pk[35 + q]));
        if ((c & 3) == 3) publish(c >> 2);
    }
    __device__ __forceinline__ void mma_a(float (&acc)[128], int s, bool first = false) const {
        const uint32_t da = desc_lo(base, 16) + s * 1024 + (s & 2) * 4096 + wg * 512;
        const uint32_t db = desc_lo(base + 32768, 8192) + s * 2048;
        wg_fence();
        wgmma_n256<HI_SW>(acc, da, db, first ? 0 : 1);
        wgmma_n256<HI_SW>(acc, da + 2, db + 128, 1);
        wgmma_n256<HI_SW>(acc, da + 4, db + 256, 1);
        wgmma_n256<HI_SW>(acc, da + 6, db + 384, 1);
        wg_commit();
    }
    __device__ __forceinline__ void mma_c(float (&acc)[88], int s, int up, bool first = false) const {
        const uint32_t da = desc_lo(base, 16) + s * 1024 + (s & 2) * 4608 + wg * 512;
        const uint32_t db = desc_lo(base + 32768, 8192) + up * 1536 + s * 3072;
        wg_fence();
        wgmma_n176<HI_SW>(acc, da, db, first ? 0 : 1);
        wgmma_n176<HI_SW>(acc, da + 2, db + 128, 1);
        wgmma_n176<HI_SW>(acc, da + 4, db + 256, 1);
        wgmma_n176<HI_SW>(acc, da + 6, db + 384, 1);
        wg_commit();
    }
    __device__ __forceinline__ void mma_b(float (&acc)[64], int s, bool first = false) const {
        const uint32_t da = desc_lo(base + 16384, 128) + s * 2048 + wg * 128, db = desc_lo(base, 8192) + s * 2048;
        wg_fence();
        wgmma_n128<HI_H>(acc, da, db, first ? 0 : 1);
        wgmma_n128<HI_H>(acc, da + 256, db + 128, 1);
        wgmma_n128<HI_H>(acc, da + 512, db + 256, 1);
        wgmma_n128<HI_H>(acc, da + 768, db + 384, 1);
        wg_commit();
    }
    __device__ __forceinline__ void step_a(float (&acc)[128], int kb) const {
        mma_a(acc, kb & 3);
        release(BAR_EMPTY_A + ((kb - 1) & 3));
    }
    __device__ __forceinline__ void next_a(int kb) const { wait_full(BAR_FULL_A + ((kb + 1) & 3), ((kb + 1) >> 2) & 1); }
};

__global__ void __launch_bounds__(NUM_THREADS, 1) geglu_ffn_kernel(const Ptrs pp, const __grid_constant__ Maps mp) {
    extern __shared__ __align__(1024) uint8_t smem_raw[];
    const int warp = __shfl_sync(0xffffffffu, threadIdx.x >> 5, 0);
    const int lane = threadIdx.x & 31;

    uint32_t sm;
    asm("mov.u32 %0, %%smid;" : "=r"(sm));
    const int tpc = sm >> 1;
    const int q7 = ((tpc - 32) * 37) >> 8;
    const bool extra = (tpc >> 1) == 30;
    const int grp = tpc < 32 ? tpc & 7 : tpc < 60 ? tpc - 31 - 7 * q7 : 0;
    const int j_blk = tpc < 32 ? tpc >> 3 : tpc < 60 ? 4 + q7 : tpc - 58;
    const int m_blk = extra ? (sm & 3) * 4 : grp * 2 + (sm & 1);
    const int col0 = extra ? 54 : j_blk * 2;

    const uint32_t full_c = bars + 8 * BAR_FULL_C, piece = bars + 8 * BAR_PIECE;
    if (warp == 8) {
        if (!extra && elect_one()) {
            const uint32_t b = base + 2 * 65536;
            mbar_init(piece, 1);
            mbar_init(piece + 8, 1);
            mbar_init(piece + 16, 1);
            mbar_init(full_c + 32, 1);
            mbar_init(full_c + 40, 1);
            asm volatile("fence.mbarrier_init.release.cluster;" ::: "memory");
            mbar_expect_tx(piece, 8192 + 6144);
            tma_2d(b + 49152, &mp.x64, piece, 0, m_blk * 128);
            tma_3d(b, &mp.g16, piece, 0, 0, col0);
            tma_3d(b + 4096, &mp.gp16, piece, 0, 0, j_blk);
            mbar_expect_tx(piece + 8, 8192);
            tma_2d(b + 57344, &mp.x64, piece + 8, 0, m_blk * 128 + 64);
            mbar_expect_tx(piece + 16, 6144);
            tma_3d(b + 6144, &mp.g16, piece + 16, 0, 16, col0);
            tma_3d(b + 10240, &mp.gp16, piece + 16, 0, 16, j_blk);
            mbar_expect_tx(full_c + 32, 12288);
            tma_3d(b + 12288, &mp.g16, full_c + 32, 0, 32, col0);
            tma_3d(b + 16384, &mp.gp16, full_c + 32, 0, 32, j_blk);
            tma_3d(b + 18432, &mp.g16, full_c + 32, 0, 48, col0);
            tma_3d(b + 22528, &mp.gp16, full_c + 32, 0, 48, j_blk);
            mbar_expect_tx(full_c + 40, 24576);
            tma_3d(b + 24576, &mp.w64[1], full_c + 40, 0, 0, col0);
            tma_3d(b + 40960, &mp.part[1], full_c + 40, 0, 0, j_blk);
#pragma unroll
            for (int i = 0; i < 4; i++) mbar_init(full_c + 8 * i, 1);
#pragma unroll
            for (int i = 0; i < 6; i++) mbar_init(bars + 8 * (BAR_EMPTY_C + i), 8);
            asm volatile("fence.mbarrier_init.release.cluster;" ::: "memory");
        }
        __syncwarp();
        asm volatile("bar.arrive 4, 384;" ::: "memory");
    } else {
        if (warp == 9 && !extra) {
            const uint8_t* p = lane < 16 ? pp.x + (m_blk * 128 + j_blk * 16 + lane) * 2048
                                         : pp.wg + (m_blk * 4 + (lane & 3)) * (D_FF * 2) + (lane < 24 ? col0 * 128 + (lane & 4) * 32 : 2048 + j_blk * 96 + (lane & 4) * 20);
            asm volatile("prefetch.global.L2 [%0];" :: "l"(p));
        }
        asm volatile("bar.sync 4, %0;" :: "r"(384) : "memory");
        asm volatile("nanosleep.u32 0;" ::: "memory");
    }

    if (warp < 8) {
        if (warp == 0) {
            if (elect_one()) {
#pragma unroll
                for (int i = 0; i < BAR_FULL_C; i++) {
                    const bool empty = (i >= BAR_EMPTY_A && i < BAR_FULL_B) || (i >= BAR_EMPTY_B && i < BAR_SFULL);
                    mbar_init(bars + 8 * i, empty ? 8 : (i >= BAR_SFULL && i < BAR_SEMPTY) ? 4 : 1);
                }
#pragma unroll
                for (int i = 1; i < 4; i++) mbar_init(bars + 8 * (BAR_POLL + i), 1);
                asm volatile("fence.mbarrier_init.release.cluster;" ::: "memory");
            }
            __syncwarp();
            asm volatile("bar.arrive 2, %0;" :: "r"(extra ? 160 : 128) : "memory");
        }
        asm volatile("setmaxnreg.inc.sync.aligned.u32 240;");
        asm volatile("bar.sync 1, 256;" ::: "memory");
        Consumer c;
        c.lane = lane;
        c.wg = warp >> 2;
        c.st_h = base + STAGING_OFF + c.wg * 16384 + (warp & 3) * 512 + (lane & 8) * 32 + (lane >> 4) * 128 + (lane & 7) * 16;
        const bool always = sm != 0xffffffffu;

        uint32_t pk[64], gp[12], up[12];
        if (extra) {
#pragma unroll
            for (int i = 4; i < 12; i++) asm volatile("" : "=r"(gp[i]), "=r"(up[i]));
#pragma unroll
            for (int i = 0; i < 64; i++) asm volatile("" : "=r"(pk[i]));
            c.wait_full(BAR_FULL_A, 0);
        } else {
            float accg[88], accu[88];
#pragma unroll
            for (int i = 0; i < 88; i++) asm volatile("" : "=f"(accg[i]), "=f"(accu[i]));
            const uint32_t da = desc_lo(base + 2 * 65536 + 49152, 16) + c.wg * 512;
            constexpr uint32_t dq = desc_lo(base + 2 * 65536, 2048);
            c.wait_full(BAR_PIECE + c.wg, 0);
            c.wait_full(BAR_PIECE, 0);
            wg_fence();
            wgmma_n176<HI_SW>(accg, da, dq, 0);
            c.wait_full(BAR_PIECE + 2, 0);
            wg_fence();
            wgmma_n176<HI_SW>(accg, da + 2, dq + 384, 1);
            c.wait_full(BAR_FULL_C + 4, 0);
            wg_fence();
            wgmma_n176<HI_SW>(accg, da + 4, dq + 768, 1);
            wgmma_n176<HI_SW>(accg, da + 6, dq + 1152, 1);
            wg_commit();
            c.wait_full(BAR_FULL_C + 5, 0);
            if (c.wg) asm volatile("bar.sync 6, 256;" ::: "memory");
            c.mma_c(accu, 2, 1, true);
            if (!c.wg) asm volatile("bar.arrive 6, 256;" ::: "memory");
            wg_wait<1>();
            c.release(BAR_EMPTY_C + 4);
            c.wait_full(BAR_FULL_C, 0);
            int s = 0, ps = 2;
            uint32_t ph = 0;
#pragma unroll 1
            for (int kb = 1; kb < 15; kb++) {
                wg_wait<0>();
                c.mma_c(accg, s, 0);
                c.release(BAR_EMPTY_C + 2 * ps + 1);
                c.wait_full(BAR_FULL_C + 2 * s + 1, ph);
                wg_wait<0>();
                c.mma_c(accu, s, 1);
                c.release(BAR_EMPTY_C + 2 * s);
                ps = s;
                if (++s == 3) s = 0;
                if (s == 2) ph ^= 1;
                c.wait_full(BAR_FULL_C + 2 * s, ph);
            }
            wg_wait<0>();
            c.mma_c(accg, 2, 0);
            c.release(BAR_EMPTY_C + 3);
            c.wait_full(BAR_FULL_C + 5, 1);
            c.mma_c(accu, 2, 1);
            wg_wait<1>();
            fence_regs<88>(accg);
            c.release(BAR_EMPTY_C + 4);
#pragma unroll
            for (int i = 0; i < 32; i++) asm volatile("" : "=r"(pk[i]));
#pragma unroll
            for (int i = 0; i < 12; i++) asm volatile("" : "=r"(gp[i]));
            if (always) {
#pragma unroll
                for (int i = 0; i < 12; i++) {
                    gp[i] = i < 4 ? gelu2(accg[64 + 2 * i], accg[65 + 2 * i]) : pack_bf16(accg[64 + 2 * i], accg[65 + 2 * i]);
                    asm volatile("" : "+r"(gp[i]));
                }
#pragma unroll
                for (int i = 0; i < 32; i++) {
                    pk[i] = pack_bf16(accg[2 * i], accg[2 * i + 1]);
                    asm volatile("" : "+r"(pk[i]));
                }
            }
            c.wait_full(BAR_FULL_A, 0);
            wg_wait<0>();
            fence_regs<88>(accu);
            c.release(BAR_EMPTY_C + 5);
#pragma unroll
            for (int i = 0; i < 12; i++) up[i] = pack_bf16(accu[64 + 2 * i], accu[65 + 2 * i]);
            stsm_x4(c.st_h + 8192, mul_bf16x2(gp[0], up[0]), mul_bf16x2(gp[1], up[1]), mul_bf16x2(gp[2], up[2]), mul_bf16x2(gp[3], up[3]));
#pragma unroll
            for (int i = 0; i < 32; i++) pk[32 + i] = pack_bf16(accu[2 * i], accu[2 * i + 1]);
        }

        float acc[128];
#pragma unroll
        for (int i = 0; i < 128; i++) asm volatile("" : "=f"(acc[i]));
        auto stage_part = [&](int i) {
            stsm_x4(c.st_h + 8192 + i * 512, geglu2(gp[i], up[i]), geglu2(gp[i + 1], up[i + 1]), geglu2(gp[i + 2], up[i + 2]), geglu2(gp[i + 3], up[i + 3]));
        };
        c.mma_a(acc, 0, true);
        c.wait_full(BAR_FULL_A + 1, 0);
        c.mma_a(acc, 1);
        if (!extra) stage_part(4);
        wg_wait<1>();
        c.release(BAR_EMPTY_A);
        if (!extra) {
            stage_part(8);
            c.publish(1);
        }
        c.wait_full(BAR_FULL_A + 2, 0);
#pragma unroll 1
        for (int t = extra ? 0 : 2;; t++) {
#pragma unroll
            for (int kb = 2; kb < 10; kb++) {
                wg_wait<0>();
                c.step_a(acc, kb);
                if (t > 0) c.stage_geglu(kb - 2, t & 1, pk);
                c.next_a(kb);
            }
#pragma unroll 1
            for (int kb = 10; kb < 15; kb++) {
                wg_wait<0>();
                c.step_a(acc, kb);
                c.next_a(kb);
            }
            if (t == 3) break;
            c.mma_a(acc, 3);
            wg_wait<1>();
            c.release(BAR_EMPTY_A + 2);
            c.wait_full(BAR_FULL_A, 0);
            wg_wait<0>();
            fence_regs<128>(acc);
            c.release(BAR_EMPTY_A + 3);
#pragma unroll
            for (int i = 0; i < 64; i++) pk[i] = pack_bf16(acc[2 * i], acc[2 * i + 1]);
            c.mma_a(acc, 0, true);
            c.wait_full(BAR_FULL_A + 1, 0);
            c.mma_a(acc, 1);
            wg_wait<1>();
            c.release(BAR_EMPTY_A);
            c.wait_full(BAR_FULL_A + 2, 0);
        }
        wg_wait<0>();
        c.step_a(acc, 15);
        auto stage_acc = [&](int q) {
            const int g = 8 * q, u = 64 + 8 * q;
            c.stage(q, 0, pack_bf16(geglu(acc[g], acc[u]), geglu(acc[g + 1], acc[u + 1])), pack_bf16(geglu(acc[g + 2], acc[u + 2]), geglu(acc[g + 3], acc[u + 3])),
                    pack_bf16(geglu(acc[g + 4], acc[u + 4]), geglu(acc[g + 5], acc[u + 5])), pack_bf16(geglu(acc[g + 6], acc[u + 6]), geglu(acc[g + 7], acc[u + 7])));
        };
        if (extra) {
            wg_wait<0>();
            fence_regs<128>(acc);
#pragma unroll
            for (int q = 0; q < 8; q++) {
                stage_acc(q);
                if ((q & 3) == 3) c.publish(q >> 2);
            }
            return;
        }
        c.wait_full(BAR_FULL_B, 0);

        constexpr int KB0 = 17;
        float acc4[64];
        uint32_t h0, h1;
#pragma unroll
        for (int kb = 0; kb < KB0; kb++) {
            wg_wait<0>();
            if (kb == 0) fence_regs<128>(acc);
            c.mma_b(acc4, kb % STB, kb == 0);
            c.release(kb == 0 ? BAR_EMPTY_A + 3 : BAR_EMPTY_B + (kb - 1) % STB);
            if (!(kb & 1)) asm volatile("" : "=r"(h0), "=r"(h1));
            if (always) {
                if (kb % 8 == 0 && kb) c.publish(kb / 8 - 1);
                if (kb < 16) {
                    const int g = 4 * kb, u = 64 + g;
                    const uint32_t r0 = pack_bf16(geglu(acc[g], acc[u]), geglu(acc[g + 1], acc[u + 1]));
                    const uint32_t r1 = pack_bf16(geglu(acc[g + 2], acc[u + 2]), geglu(acc[g + 3], acc[u + 3]));
                    if (kb & 1) {
                        c.stage(kb >> 1, 0, h0, h1, r0, r1);
                    } else {
                        h0 = r0;
                        h1 = r1;
                        asm volatile("" : "+r"(h0), "+r"(h1));
                    }
                }
            }
            c.wait_full(BAR_FULL_B + (kb + 1) % STB, ((kb + 1) / STB) & 1);
        }
        int s = KB0 % STB, ps = (KB0 - 1) % STB;
        uint32_t ph = (KB0 / STB) & 1;
#pragma unroll 1
        for (int kb = KB0; kb < KB_FF - TN; kb++) {
            wg_wait<0>();
            c.mma_b(acc4, s);
            c.release(BAR_EMPTY_B + ps);
            ps = s;
            if (++s == STB) { s = 0; ph ^= 1; }
            c.wait_full(BAR_FULL_B + s, ph);
        }
        c.wait_full(BAR_SEMPTY + 2 * c.wg, 1);
        c.wait_full(BAR_SEMPTY + 2 * c.wg + 1, 1);
        const uint32_t strip = base + STAGING_OFF + c.wg * 16384 + (warp & 3) * 2048;
        const uint32_t st_row = strip + (lane & 15) * 128, st_sw = ((lane >> 4) ^ (lane & 7)) << 4;
        const int row0 = m_blk * 128 + warp * 16;
        const uint32_t ld_row = base + STAGING_OFF + 16384 + (warp & 3) * 2048 + (lane >> 3) * 128 + (((lane & 7) ^ (lane >> 3)) << 4);
        uint8_t* optr = pp.o + (size_t)((row0 | 64) + (lane >> 3)) * 2048 + j_blk * 256 + (lane & 7) * 16;
        auto stage_out = [&](int h) {
#pragma unroll
            for (int q = 0; q < 4; q++) {
                const int i = 32 * h + 8 * q;
                stsm_x4(st_row + h * 8192 + (st_sw ^ (q << 5)), pack_bf16(acc4[i], acc4[i + 1]), pack_bf16(acc4[i + 2], acc4[i + 3]),
                        pack_bf16(acc4[i + 4], acc4[i + 5]), pack_bf16(acc4[i + 6], acc4[i + 7]));
            }
        };
        auto store_out = [&](int h) {
            uint4 v[4];
#pragma unroll
            for (int i = 0; i < 4; i++)
                asm volatile("ld.shared.v4.u32 {%0, %1, %2, %3}, [%4];" : "=r"(v[i].x), "=r"(v[i].y), "=r"(v[i].z), "=r"(v[i].w)
                             : "r"((ld_row ^ ((i & 1) << 6)) + i * 512 + h * 8192) : "memory");
#pragma unroll
            for (int i = 0; i < 4; i++)
                asm volatile("st.global.v4.u32 [%0], {%1, %2, %3, %4};" :: "l"(optr + i * 8192 + h * 128), "r"(v[i].x), "r"(v[i].y), "r"(v[i].z), "r"(v[i].w) : "memory");
        };
        wg_wait<0>();
        if (!c.wg) {
#pragma unroll
            for (int kb = KB_FF - TN; kb < KB_FF; kb++) {
                if (kb > KB_FF - TN) c.wait_full(BAR_FULL_B + kb % STB, (kb / STB) & 1);
                c.mma_b(acc4, kb % STB);
            }
            asm volatile("bar.arrive 6, 256;" ::: "memory");
            wg_wait<0>();
            fence_regs<64>(acc4);
#pragma unroll
            for (int h = 0; h < 2; h++) {
                stage_out(h);
                fence_async_smem();
                __syncwarp();
                if (elect_one()) {
                    tma_store_2d(&mp.out, strip + h * 8192, j_blk * 128 + h * 64, row0);
                    bulk_commit();
                }
            }
            asm volatile("bar.sync %0, 64;" :: "r"(7 + warp) : "memory");
            if (elect_one()) {
                fence_async_smem();
                tma_store_2d(&mp.out, strip + 16384, j_blk * 128, row0 + 64);
                bulk_commit();
            }
            if (elect_one()) asm volatile("cp.async.bulk.wait_group.read 0;" ::: "memory");
            __syncwarp();
        } else {
            float half[2][32];
            uint32_t af[16 * TR];
            const uint32_t ld_h = c.st_h - STAGING_OFF + 2048;
#pragma unroll
            for (int kb = KB_FF - TN; kb < KB_FF; kb++) {
                if (kb > KB_FF - TN) c.wait_full(BAR_FULL_B + kb % STB, (kb / STB) & 1);
#pragma unroll
                for (int q = 4 * (kb - KB_FF + TR); q >= 0 && q < 4 * (kb + 1 - KB_FF + TR); q++)
                    asm volatile("ldmatrix.sync.aligned.m8n8.x4.shared.b16 {%0, %1, %2, %3}, [%4];"
                                 : "=r"(af[4 * q]), "=r"(af[4 * q + 1]), "=r"(af[4 * q + 2]), "=r"(af[4 * q + 3])
                                 : "r"(ld_h + (kb % STB) * 32768 + (q & 3) * 4096) : "memory");
            }
            auto mma_half = [&](int h, int q0, int q1) {
                wg_fence();
#pragma unroll
                for (int q = q0; q < q1; q++)
                    wgmma_n64_rs(half[h], af + 4 * q, desc_lo(base, 8192) + ((KB_FF - TR + (q >> 2)) % STB) * 2048 + h * 512 + (q & 3) * 128, h | q);
                wg_commit();
            };
            auto merge_half = [&](int h) {
                fence_regs<32>(half[h]);
#pragma unroll
                for (int i = 0; i < 32; i++) acc4[32 * h + i] = h ? half[h][i] : acc4[32 * h + i] + half[h][i];
            };
            asm volatile("bar.sync 6, 256;" ::: "memory");
#pragma unroll
            for (int kb = KB_FF - TN; kb < KB_FF - TR; kb++) c.mma_b(acc4, kb % STB);
            mma_half(0, 0, 4 * TR);
            wg_wait<1>();
            fence_regs<64>(acc4);
#pragma unroll
            for (int i = 0; i < 32; i++) asm volatile("mov.f32 %0, %1;" : "=f"(half[1][i]) : "f"(acc4[32 + i]));
            mma_half(1, 0, RB);
            wg_wait<1>();
            merge_half(0);
            stage_out(0);
            mma_half(1, RB, 4 * TR);
            asm volatile("bar.arrive %0, 64;" :: "r"(3 + warp) : "memory");
            wg_wait<0>();
            merge_half(1);
            stage_out(1);
            __syncwarp();
            store_out(1);
        }
    } else {
        asm volatile("setmaxnreg.dec.sync.aligned.u32 24;");
        if (warp != 8) {
            asm volatile("bar.sync 2, %0;" :: "r"(extra ? 160 : 128) : "memory");
            uint32_t cnt;
            if (warp == 11) asm volatile("ld.relaxed.gpu.global.u32 %0, [%1];" : "=r"(cnt) : "l"(g_ready + m_blk * 4) : "memory");
            asm volatile("bar.sync 5, 96;" ::: "memory");
            if (elect_one()) {
                if (warp <= 10) {
                    const int w = warp - 9;
                    if (!extra) mbar_arrive(bars + 8 * (BAR_SEMPTY + 2 * w));
#pragma unroll 1
                    for (int b = extra ? 0 : 1; b < 8; b++) {
                        const int t = b >> 1;
                        const bool part = !extra && b == 1;
                        const int m = extra ? m_blk + t : m_blk;
                        const int chunk = part ? 64 + 3 * j_blk : (col0 + (b & 1) + (extra || t == 1 ? 0 : 16 * t - 10)) * 4;
                        uint8_t* dst = g_h + ((size_t)m * (KB_FF * 4) + chunk) * 4096 + w * 2048;
                        const uint32_t src = base + STAGING_OFF + w * 16384 + (b & 1) * 8192;
                        const uint32_t pace = t < 3 ? 300 : 0;
                        mbar_wait_p(bars + 8 * (BAR_SFULL + 2 * w + (b & 1)), (extra ? t : t + b + 1) & 1);
#pragma unroll 1
                        for (int q = 0; q < (part ? 3 : 4); q++) {
                            if (q | (b & 1)) __nanosleep(pace);
                            bulk_store(dst + q * 4096, src + q * 2048, 2048);
                            bulk_commit();
                            asm volatile("cp.async.bulk.wait_group.read 0;" ::: "memory");
                        }
                        mbar_arrive(bars + 8 * (BAR_SEMPTY + 2 * w + (b & 1)));
                        if ((b & 1) && !part) {
                            asm volatile("cp.async.bulk.wait_group 0;" ::: "memory");
                            asm volatile("fence.proxy.async.global;" ::: "memory");
                            asm volatile("red.release.gpu.global.add.u32 [%0], %1;"
                                         :: "l"(g_ready + m * 4 + (extra ? 3 : t - 1)), "r"(extra ? 16 : 2) : "memory");
                        }
                    }
                } else {
                    uint32_t nsm;
                    asm("mov.u32 %0, %%nsmid;" : "=r"(nsm));
                    if (smem_u32(smem_raw) != base || nsm != NUM_CTAS) __trap();
                    prefetch_map(&mp.d);
                    prefetch_map(&mp.out);
                    if (extra) return;
                    const int row = m_blk * 64 + j_blk * 8;
#pragma unroll 1
                    for (int t = 0; t < 2; t++) {
                        mbar_wait_p(bars + 8 * (BAR_PF + t), 0);
#pragma unroll 1
                        for (int r = (row + 768 - 256 * t) & 1023, e = r + 8; r < e; r++) {
                            prefetch_l2(pp.wg + r * (D_FF * 2) + 2816 + t * 2048, 2048);
                            prefetch_l2(pp.wu + r * (D_FF * 2) + 2816 + t * 2048, 2048);
                        }
                    }
                    mbar_wait_p(bars + 8 * (BAR_PF + 2), 0);
                    prefetch_l2(pp.wd + row * 2048, 16384);
#pragma unroll 1
                    for (int round = 0; round < 4; round++) {
                        uint32_t v, it = 0;
                        if (round) mbar_wait_p(bars + 8 * (BAR_POLL + round), 0);
                        while (true) {
                            asm volatile("ld.acquire.gpu.global.u32 %0, [%1];" : "=r"(v) : "l"(g_ready + m_blk * 4 + round) : "memory");
                            if (v - (cnt & ~31u) >= 32u) break;
                            if (++it > (1u << 20)) __trap();
                            __nanosleep(200);
                        }
                        asm volatile("fence.proxy.async.global;" ::: "memory");
                        mbar_arrive(bars + 8 * (BAR_HREADY + round));
                    }
                }
            }
            return;
        }
        if (extra) asm volatile("bar.sync 2, 160;" ::: "memory");
        if (!elect_one()) return;
        if (extra) __nanosleep(2000);
        if (!extra) {
            int s = 0;
            uint32_t ph = 1;
#pragma unroll 1
            for (int i = 2; i < 32; i++) {
                const uint32_t full = full_c + 8 * s, bx = base + (s >> 1) * 16384 + (s & 4) * 36864;
                const uint32_t bw = base + 32768 + s * 24576;
                if (s == 4) ph ^= 1;
                if (i == 4) mbar_wait_p(piece, 0);
                mbar_wait_p(bars + 8 * (BAR_EMPTY_C + s), ph);
                if (i & 1) tma_2d(bx, &mp.x128, full - 8, (i >> 1) * 64, m_blk * 128);
                mbar_expect_tx(full, (i & 1) ? 24576 : 40960);
                tma_3d(bw, &mp.w64[i & 1], full, 0, (i >> 1) * 64, col0);
                tma_3d(bw + 16384, &mp.part[i & 1], full, 0, (i >> 1) * 64, j_blk);
                if (i == 8 + ((3 * m_blk) >> 1)) mbar_arrive(bars + 8 * BAR_PF);
                if ((i & 1) == 0 && i >= 4 && (i >> 1) + 1 < 16)
                    prefetch_l2(((j_blk & 1) ? pp.wu : pp.wg) + (((i >> 1) + 1) * 64 + m_blk * 4 + (j_blk >> 1)) * (D_FF * 2), 2816);
                if (++s == 6) s = 0;
            }
        }
#pragma unroll 1
        for (int i = 0; i < (extra ? 64 : 32); i++) {
            const int s = i & 3, t = i >> 4, k0 = ((((i & 12) | ((0xc9 >> 2 * s) & 3)) + 12 - 4 * t) & 15) * 64;
            const bool keep = !extra && (i == 1 || (i >> 2) == 4 || i == 0 || i == 3);
            const int c0 = extra ? col0 : col0 + 16 * t + 22;
            const uint32_t full = bars + 8 * (BAR_FULL_A + s), b = base + 32768 + s * 32768;
            if (i < 4 && !extra) {
                if (i < 3) mbar_wait_p(bars + 8 * (BAR_EMPTY_C + i + 1), 0);
            } else {
                mbar_wait_p(bars + 8 * (BAR_EMPTY_A + s), ((i >> 2) & 1) ^ 1);
            }
            mbar_expect_tx(full, keep ? 32768 : 49152);
            tma_3d(b, &mp.w64[0], full, 0, k0, c0);
            tma_3d(b + 16384, &mp.w64[1], full, 0, k0, c0);
            if (i == 2 && !extra) mbar_wait_p(bars + 8 * (BAR_EMPTY_C + 5), 1);
            if (!keep) tma_2d(base + s * 16384 + (s & 2) * 65536, &mp.x128, full, k0, (extra ? m_blk + t : m_blk) * 128);
            if (i == 4 + m_blk) mbar_arrive(bars + 8 * (BAR_PF + 1));
            if (i == 20 + (m_blk >> 1)) mbar_arrive(bars + 8 * (BAR_PF + 2));
        }
        if (extra) return;
        const uint8_t* h_src = g_h + (size_t)m_blk * KB_FF * 16384;
        int s = 0;
        uint32_t ph = 1;
#pragma unroll 1
        for (int i = 0; i < KB_FF; i++) {
            const uint32_t full = bars + 8 * (BAR_FULL_B + s);
            if (i < STB) mbar_wait_p(bars + 8 * (BAR_EMPTY_A + (i == 0 ? 1 : (2 * i + 1) / 3)), 1);
            else mbar_wait_p(bars + 8 * (BAR_EMPTY_B + s), ph);
            mbar_expect_tx(full, 32768);
            tma_3d(base + s * 32768, &mp.d, full, 0, i * 64, col0);
            if (i == 0 || (i & 15) == 6) mbar_wait_p(bars + 8 * (BAR_HREADY + (i >> 4)), 0);
            bulk_load(base + s * 32768 + 16384, h_src + (size_t)i * 16384, 16384, full);
            if (i >= 16 && (i & 15) == 2) mbar_arrive(bars + 8 * (BAR_POLL + (i >> 4)));
            if (++s == STB) { s = 0; ph ^= 1; }
        }
    }
}

typedef CUresult (*EncodeFn)(CUtensorMap*, CUtensorMapDataType, cuuint32_t, void*, const cuuint64_t*, const cuuint64_t*,
                             const cuuint32_t*, const cuuint32_t*, CUtensorMapInterleave, CUtensorMapSwizzle,
                             CUtensorMapL2promotion, CUtensorMapFloatOOBfill);

void map_2d(EncodeFn enc, CUtensorMap* m, const void* p, int rows, int cols, int box_rows) {
    cuuint64_t dims[2] = {(cuuint64_t)cols, (cuuint64_t)rows};
    cuuint64_t str[1] = {(cuuint64_t)cols * 2};
    cuuint32_t box[2] = {64, (cuuint32_t)box_rows};
    cuuint32_t es[2] = {1, 1};
    enc(m, CU_TENSOR_MAP_DATA_TYPE_BFLOAT16, 2, const_cast<void*>(p), dims, str, box, es, CU_TENSOR_MAP_INTERLEAVE_NONE,
        CU_TENSOR_MAP_SWIZZLE_128B, CU_TENSOR_MAP_L2_PROMOTION_L2_128B, CU_TENSOR_MAP_FLOAT_OOB_FILL_NONE);
}
void map_w(EncodeFn enc, CUtensorMap* m, const void* p, int K, int N, int rows, int atoms) {
    cuuint64_t dims[3] = {64, (cuuint64_t)K, (cuuint64_t)N / 64};
    cuuint64_t str[2] = {(cuuint64_t)N * 2, 128};
    cuuint32_t box[3] = {64, (cuuint32_t)rows, (cuuint32_t)atoms};
    cuuint32_t es[3] = {1, 1, 1};
    enc(m, CU_TENSOR_MAP_DATA_TYPE_BFLOAT16, 3, const_cast<void*>(p), dims, str, box, es, CU_TENSOR_MAP_INTERLEAVE_NONE,
        CU_TENSOR_MAP_SWIZZLE_128B, CU_TENSOR_MAP_L2_PROMOTION_L2_128B, CU_TENSOR_MAP_FLOAT_OOB_FILL_NONE);
}

void map_part(EncodeFn enc, CUtensorMap* m, const void* p, int rows) {
    cuuint64_t dims[3] = {48, (cuuint64_t)D_MODEL, 8};
    cuuint64_t str[2] = {(cuuint64_t)D_FF * 2, 96};
    cuuint32_t box[3] = {64, (cuuint32_t)rows, 1};
    cuuint32_t es[3] = {1, 1, 1};
    enc(m, CU_TENSOR_MAP_DATA_TYPE_BFLOAT16, 3, (char*)const_cast<void*>(p) + 1024 * 2, dims, str, box, es, CU_TENSOR_MAP_INTERLEAVE_NONE,
        CU_TENSOR_MAP_SWIZZLE_128B, CU_TENSOR_MAP_L2_PROMOTION_L2_128B, CU_TENSOR_MAP_FLOAT_OOB_FILL_NONE);
}

}

extern "C" void kernel_launch(void* const* d_in, const int* in_sizes, int n_in, void* d_out, int out_size) {
    (void)in_sizes; (void)n_in; (void)out_size;
    void* fn = nullptr;
    cudaDriverEntryPointQueryResult st;
    cudaGetDriverEntryPoint("cuTensorMapEncodeTiled", &fn, cudaEnableDefault, &st);
    EncodeFn enc = (EncodeFn)fn;
    Maps mp;
    map_2d(enc, &mp.x64, d_in[0], M_TOK, D_MODEL, 64);
    map_2d(enc, &mp.x128, d_in[0], M_TOK, D_MODEL, 128);
    map_w(enc, &mp.g16, d_in[1], D_MODEL, D_FF, 16, 2);
    map_part(enc, &mp.gp16, d_in[1], 16);
    map_w(enc, &mp.w64[0], d_in[1], D_MODEL, D_FF, 64, 2);
    map_w(enc, &mp.w64[1], d_in[2], D_MODEL, D_FF, 64, 2);
    map_part(enc, &mp.part[0], d_in[1], 64);
    map_part(enc, &mp.part[1], d_in[2], 64);
    map_w(enc, &mp.d, d_in[3], D_FF, D_MODEL, 64, 2);
    map_2d(enc, &mp.out, d_out, M_TOK, D_MODEL, 16);
    const Ptrs pp = {(const uint8_t*)d_in[1], (const uint8_t*)d_in[2], (const uint8_t*)d_in[3], (uint8_t*)d_out, (const uint8_t*)d_in[0]};
    cudaFuncSetAttribute(geglu_ffn_kernel, cudaFuncAttributeMaxDynamicSharedMemorySize, SMEM_BYTES);
    geglu_ffn_kernel<<<NUM_CTAS, NUM_THREADS, SMEM_BYTES>>>(pp, mp);
}
```
